```python
import torch

def _softmax(x, axis=-1):
    return torch.softmax(x, dim=axis)
def _gelu(x):
    return torch.nn.functional.gelu(x, approximate="tanh")
def _silu(x):
    return torch.nn.functional.silu(x)
def _sigmoid(x):
    return torch.sigmoid(x)
def _layernorm(x, axis=-1, eps=1e-5):
    m = x.mean(dim=axis, keepdim=True)
    v = x.var(dim=axis, keepdim=True, unbiased=False)
    return (x - m) / torch.sqrt(v + eps)
def _scatter_add(tgt, idx, src, axis=0):
    return tgt.clone().index_add_(axis, idx, src)
def _segment_sum(src, seg, n):
    out = torch.zeros((n,) + src.shape[1:], dtype=src.dtype)
    return out.index_add_(0, seg, src)
def _pad(x, pw):
    flat = tuple(v for pair in reversed(pw) for v in pair)
    return torch.nn.functional.pad(x, flat)

kernel_name = 'sequential_preLN__ssm_conv_s4d__geglu_ffn__prompt'

def setup_inputs():

    _w = (lambda a: (lambda t: t.to(torch.bfloat16) if t.is_floating_point() else t)(torch.as_tensor(a)))
    def _A_setup():
        Bsz, L, D, N = 1, 2048, 512, 128
        return {
            "u": _w((lambda *s: torch.randn(*s, dtype=torch.bfloat16) * 0.05)(Bsz, L, D)),
            "log_A_real": _w((lambda *s: torch.randn(*s, dtype=torch.bfloat16) * 6.4)(D, N) * 0.5),
            "A_imag": _w((lambda *s: torch.randn(*s, dtype=torch.bfloat16) * 0.05)(D, N) * 3.14),
            "C_real": _w((lambda *s: torch.randn(*s, dtype=torch.bfloat16) * 0.05)(D, N) / N ** 0.5),
            "C_imag": _w((lambda *s: torch.randn(*s, dtype=torch.bfloat16) * 0.05)(D, N) / N ** 0.5),
            "log_dt": _w((lambda *s: torch.randn(*s, dtype=torch.bfloat16) * 0.05)(D) * 0.5 - 4.0),
            "D_skip": _w((lambda *s: torch.randn(*s, dtype=torch.bfloat16) * 0.05)(D)),
        }
    _A_in = _A_setup()

    def _B_setup():
        B, S, D, F = 1, 2048, 512, 1376
        return {
            "x": _w((lambda *s: torch.randn(*s, dtype=torch.bfloat16) * 0.05)(B, S, D)),
            "w_gate": _w((lambda *s: torch.randn(*s, dtype=torch.bfloat16) * 0.05)(D, F)),
            "w_up": _w((lambda *s: torch.randn(*s, dtype=torch.bfloat16) * 0.05)(D, F)),
            "w_down": _w((lambda *s: torch.randn(*s, dtype=torch.bfloat16) * 0.05)(F, D)),
        }
    _B_in = _B_setup()

    return {
        "A_u": _A_in["u"],
        "A_log_A_real": _A_in["log_A_real"],
        "A_A_imag": _A_in["A_imag"],
        "A_C_real": _A_in["C_real"],
        "A_C_imag": _A_in["C_imag"],
        "A_log_dt": _A_in["log_dt"],
        "A_D_skip": _A_in["D_skip"],
        "B_x": _B_in["x"],
        "B_w_gate": _B_in["w_gate"],
        "B_w_up": _B_in["w_up"],
        "B_w_down": _B_in["w_down"],
    }

def reference(A_u, A_log_A_real, A_A_imag, A_C_real, A_C_imag, A_log_dt, A_D_skip, B_x, B_w_gate, B_w_up, B_w_down):
    def _A_ref(u, log_A_real, A_imag, C_real, C_imag, log_dt, D_skip):
        L = u.shape[1]
        dt = torch.exp(log_dt)
        A = -torch.exp(log_A_real) + 1j * A_imag
        C = (C_real + 1j * C_imag) * dt[:, None]
        pos = (lambda x, dt: x.to(dt))(torch.arange(L), log_dt.dtype)
        P = torch.exp((A * dt[:, None])[:, :, None] * pos[None, None, :])
        K = 2.0 * torch.einsum("dn,dnl->dl", C, P).real
        L2 = 2 * L
        u_t = (lambda x, *d: x.permute(*d))(u, 0, 2, 1)
        Kf = (lambda x, *a, **k: torch.fft.rfft(x.float(), *a, **k))(K, L2)
        Uf = (lambda x, *a, **k: torch.fft.rfft(x.float(), *a, **k))(u_t, L2)
        y = (lambda x, *a, **k: torch.fft.irfft(x, *a, **k).to(torch.bfloat16))(Uf * Kf[None, :, :], L2)[:, :, :L]
        y = (lambda x, *d: x.permute(*d))(y, 0, 2, 1)
        return y + u * D_skip[None, None, :]

    def _B_ref(x, w_gate, w_up, w_down):
        return (_gelu(x @ w_gate) * (x @ w_up)) @ w_down

    x = A_u
    h = x + _A_ref(_layernorm(x, axis=-1), A_log_A_real, A_A_imag, A_C_real, A_C_imag, A_log_dt, A_D_skip)
    h2 = h + _B_ref(_layernorm(h, axis=-1), B_w_gate, B_w_up, B_w_down)
    return h2
```

```cpp
#include <cuda_runtime.h>
#include <cuda_bf16.h>
#include <cuda_fp16.h>
#include <cuda.h>
#include <stdint.h>

namespace {

constexpr int kL = 2048, kD = 512, kF = 1376;
constexpr int kCtas = 128, kThreads = 384;
#define NINIT0 72
#define DLO 600
#define DHI 0
#define KUNROLL 1
#define MAP 3
#define WPF 2
#define GATE2 0
#define GATE3 0
#define PST 7
#define PACE 4
#define RH "40"
#define RC "232"
#define CORD 1
#define WG0 0
#define PP 1
#define RESPOS 0
#define GS 16
#define GSPOS 7
#define PACEE 1
#define PACE3 1
#define LATEI 0
#define XH ".L2::256B"
#define NWW 3
#define WV 0
#define LATEW 1
#define XW 2
#define WST 1
#define FINB 0
#define PG2 0
#define H3P 1
#define HIOFF 32
#define RST 3
#define RSTW 1
#define STRICT 1
#define GA 7
#define PW 3
#define POLL2 0
#define SPLITF 1
#define SF 1
#define PPOS 1
#define GOFF 0
#define FAST1 1
#define STF 0
#define SPP 1
#define NQ 2
#define ONEF 0
#define PF 1
#define HDRY 0
#define DCS 5000
#define XUP 40
constexpr int kUnroll = KUNROLL;
constexpr int kSpin = 1 << 16;

constexpr uint32_t sb = 1024;
constexpr int SM_RING = 0;
constexpr int SM_KG = 0;
constexpr int SM_PART = 65536;
constexpr int SM_XT = 131072;
constexpr int SM_XST = 131072;
constexpr int SM_WS = 147456;
constexpr int SM_XS = 196608;
constexpr int SM_HST = 196608;
constexpr int XS_STEP = 25600;
constexpr int SM_V = 204800;
constexpr int SM_OST = 204800;
constexpr int SM_CS = 230400;
constexpr int SM_BAR = 231808;
constexpr int SM_MISC = 232416;
constexpr int SM_TOTAL = 232448;
constexpr int V_PITCH = 2176;
constexpr uint32_t bars = sb + SM_BAR;
constexpr int B_FULL1 = 0, B_FULL2 = 12, B_HRDY = 20, B_HEMPTY = 22, B_XFULL = 24,
              B_EMPTY1 = 32,
              B_EMPTY2 = 44, B_HFULL = 60, B_V = 62, B_XFREE = 64, B_CS = 72, B_WS = 75, B_NUM = 76;
constexpr int C_LO = 0, C_H = 2, C_CS = 50, C_G2 = 74;

struct Scratch {
  unsigned cnt[96 * 32];
  uint4 xt[kCtas * 1024];
  uint4 h[kCtas * 1024];
  uint4 H[16 * 3 * 8 * 1024];
  uint4 wp[8 * 8 * 768];
  uint4 stats[kCtas * 8];
  uint4 st2[16 * 8 * 8 * 8];
  float4 cs[8 * 96];
};
__device__ __align__(1024) Scratch g_scratch;

#define FM 0u
#define PROF(n) do { if ((FM >> (n)) & 1) asm volatile("{.reg .u32 t; mov.u32 t, %%clock; st.shared.u32 [%0], t;}" ::"r"(sb + SM_MISC + 4) : "memory"); } while (0)
#define PROFT(n) PROF(n)
#define PROFV(n, c) PROF(c)
#define PROF_ARG
#define PROF_PASS
#define PROFG(n)

#define PROF2(n)

#define chaos()

__device__ __forceinline__ void mbar_init(uint32_t b, int c) { asm volatile("mbarrier.init.shared::cta.b64 [%0], %1;" ::"r"(b), "r"(c)); }
__device__ __forceinline__ void mbar_expect(uint32_t b, uint32_t n) { asm volatile("mbarrier.arrive.expect_tx.shared::cta.b64 _, [%0], %1;" ::"r"(b), "r"(n) : "memory"); }
__device__ __forceinline__ void mbar_arrive(uint32_t b) { asm volatile("mbarrier.arrive.shared::cta.b64 _, [%0];" ::"r"(b) : "memory"); }
__device__ __forceinline__ bool mbar_try(uint32_t b, int ph) {
  uint32_t ok;
  asm volatile("{.reg .pred p; mbarrier.try_wait.parity.shared::cta.b64 p, [%1], %2; selp.u32 %0, 1, 0, p;}" : "=r"(ok) : "r"(b), "r"(ph) : "memory");
  return ok;
}
__device__ __forceinline__ void mbar_wait(uint32_t b, int ph) {
#pragma unroll 1
  for (int it = 0; !mbar_try(b, ph) && it < kSpin; it++) {}
  chaos();
}
__device__ __forceinline__ void mbar_wait_data(uint32_t b, int ph) {
  while (!mbar_try(b, ph)) {}
}
__device__ __forceinline__ bool elect() {
  uint32_t p;
  asm volatile("{.reg .pred p; elect.sync _|p, 0xffffffff; selp.u32 %0, 1, 0, p;}" : "=r"(p));
  return p;
}
__device__ __forceinline__ void bar_sync(int id, int n) { chaos(); asm volatile("bar.sync %0, %1;" ::"r"(id), "r"(n) : "memory"); chaos(); }
__device__ __forceinline__ void bar_arrive(int id, int n) { chaos(); asm volatile("bar.arrive %0, %1;" ::"r"(id), "r"(n) : "memory"); chaos(); }
__device__ __forceinline__ void bulk_g2s(uint32_t dst, const void* src, uint32_t n, uint32_t bar) {
  asm volatile("cp.async.bulk.shared::cluster.global.mbarrier::complete_tx::bytes [%0], [%1], %2, [%3];" ::"r"(dst), "l"(src), "r"(n), "r"(bar) : "memory");
}
__device__ __forceinline__ void tma2d(uint32_t dst, const CUtensorMap* m, int c0, int c1, uint32_t bar) {
  asm volatile("cp.async.bulk.tensor.2d.shared::cluster.global.mbarrier::complete_tx::bytes [%0], [%1, {%3, %4}], [%2];" ::"r"(dst), "l"(m), "r"(bar), "r"(c0), "r"(c1) : "memory");
}
__device__ __forceinline__ void fence_async() { asm volatile("fence.proxy.async.shared::cta;" ::: "memory"); }
__device__ __forceinline__ void wg_fence() { asm volatile("wgmma.fence.sync.aligned;" ::: "memory"); }
__device__ __forceinline__ void wg_commit() { asm volatile("wgmma.commit_group.sync.aligned;" ::: "memory"); }
template <int N> __device__ __forceinline__ void wg_wait() { asm volatile("wgmma.wait_group.sync.aligned %0;" ::"n"(N) : "memory"); }
__device__ __forceinline__ uint64_t mkdesc(uint32_t addr, uint32_t lbo, uint32_t sbo, int mode) {
  return (uint64_t)((addr & 0x3FFFF) >> 4) | ((uint64_t)(lbo >> 4) << 16) | ((uint64_t)(sbo >> 4) << 32) | ((uint64_t)mode << 62);
}
__device__ __forceinline__ uint32_t lds32(uint32_t a) { uint32_t v; asm volatile("ld.shared.u32 %0, [%1];" : "=r"(v) : "r"(a) : "memory"); return v; }
__device__ __forceinline__ uint2 lds64(uint32_t a) { uint2 v; asm volatile("ld.shared.v2.u32 {%0,%1}, [%2];" : "=r"(v.x), "=r"(v.y) : "r"(a) : "memory"); return v; }
__device__ __forceinline__ uint4 lds128(uint32_t a) { uint4 v; asm volatile("ld.shared.v4.u32 {%0,%1,%2,%3}, [%4];" : "=r"(v.x), "=r"(v.y), "=r"(v.z), "=r"(v.w) : "r"(a) : "memory"); return v; }
__device__ __forceinline__ void sts32(uint32_t a, uint32_t v) { asm volatile("st.shared.u32 [%0], %1;" ::"r"(a), "r"(v) : "memory"); }
__device__ __forceinline__ void sts64(uint32_t a, uint32_t x, uint32_t y) { asm volatile("st.shared.v2.u32 [%0], {%1,%2};" ::"r"(a), "r"(x), "r"(y) : "memory"); }
__device__ __forceinline__ void sts128(uint32_t a, uint32_t x, uint32_t y, uint32_t z, uint32_t w) { asm volatile("st.shared.v4.u32 [%0], {%1,%2,%3,%4};" ::"r"(a), "r"(x), "r"(y), "r"(z), "r"(w) : "memory"); }
__device__ __forceinline__ void ldsm4(uint32_t a, uint32_t* r) { asm volatile("ldmatrix.sync.aligned.m8n8.x4.shared.b16 {%0,%1,%2,%3}, [%4];" : "=r"(r[0]), "=r"(r[1]), "=r"(r[2]), "=r"(r[3]) : "r"(a) : "memory"); }
__device__ __forceinline__ void ldsm4t(uint32_t a, uint32_t* r) { asm volatile("ldmatrix.sync.aligned.m8n8.x4.trans.shared.b16 {%0,%1,%2,%3}, [%4];" : "=r"(r[0]), "=r"(r[1]), "=r"(r[2]), "=r"(r[3]) : "r"(a) : "memory"); }
__device__ __forceinline__ void stsm4(uint32_t a, uint32_t x, uint32_t y, uint32_t z, uint32_t w) { asm volatile("stmatrix.sync.aligned.m8n8.x4.shared.b16 [%0], {%1,%2,%3,%4};" ::"r"(a), "r"(x), "r"(y), "r"(z), "r"(w) : "memory"); }
__device__ __forceinline__ void stsm4t(uint32_t a, uint32_t x, uint32_t y, uint32_t z, uint32_t w) { asm volatile("stmatrix.sync.aligned.m8n8.x4.trans.shared.b16 [%0], {%1,%2,%3,%4};" ::"r"(a), "r"(x), "r"(y), "r"(z), "r"(w) : "memory"); }
__device__ __forceinline__ void mma_f16(float* d, const uint32_t* a, uint32_t b0, uint32_t b1) {
  asm volatile("mma.sync.aligned.m16n8k16.row.col.f32.f16.f16.f32 {%0,%1,%2,%3}, {%4,%5,%6,%7}, {%8,%9}, {%0,%1,%2,%3};"
               : "+f"(d[0]), "+f"(d[1]), "+f"(d[2]), "+f"(d[3]) : "r"(a[0]), "r"(a[1]), "r"(a[2]), "r"(a[3]), "r"(b0), "r"(b1));
}
__device__ __forceinline__ void mma_bf16(float* d, uint32_t a0, uint32_t a1, uint32_t a2, uint32_t a3, uint32_t b0, uint32_t b1) {
  asm volatile("mma.sync.aligned.m16n8k16.row.col.f32.bf16.bf16.f32 {%0,%1,%2,%3}, {%4,%5,%6,%7}, {%8,%9}, {%0,%1,%2,%3};"
               : "+f"(d[0]), "+f"(d[1]), "+f"(d[2]), "+f"(d[3]) : "r"(a0), "r"(a1), "r"(a2), "r"(a3), "r"(b0), "r"(b1));
}
__device__ __forceinline__ void st_relaxed128(void* p, uint32_t x, uint32_t y, uint32_t z, uint32_t w) {
  asm volatile("st.relaxed.gpu.global.v4.u32 [%0], {%1,%2,%3,%4};" ::"l"(p), "r"(x), "r"(y), "r"(z), "r"(w) : "memory");
}
__device__ __forceinline__ void bulk_s2g(const void* dst, uint32_t src, uint32_t n) {
  chaos();
  asm volatile("cp.async.bulk.global.shared::cta.bulk_group [%0], [%1], %2;" ::"l"(dst), "r"(src), "r"(n) : "memory");
  asm volatile("cp.async.bulk.commit_group;" ::: "memory");
}
__device__ __forceinline__ void bulk_wait_signal(unsigned* cnt, unsigned n) {
  asm volatile("cp.async.bulk.wait_group 0;" ::: "memory");
  chaos();
  asm volatile("red.relaxed.gpu.global.add.u32 [%0], %1;" ::"l"(cnt), "r"(n) : "memory");
}
__device__ __forceinline__ void prefetch_l2(const void* p, uint32_t n) { asm volatile("cp.async.bulk.prefetch.L2.global [%0], %1;" ::"l"(p), "r"(n) : "memory"); }
__device__ __forceinline__ uint32_t pack_h2(float lo, float hi) { uint32_t r; asm("cvt.rn.f16x2.f32 %0, %1, %2;" : "=r"(r) : "f"(hi), "f"(lo)); return r; }
__device__ __forceinline__ uint32_t pack_b2(float lo, float hi) { uint32_t r; asm("cvt.rn.bf16x2.f32 %0, %1, %2;" : "=r"(r) : "f"(hi), "f"(lo)); return r; }
__device__ __forceinline__ float blo(uint32_t v) { return __uint_as_float(v << 16); }
__device__ __forceinline__ float bhi(uint32_t v) { return __uint_as_float(v & 0xffff0000u); }
__device__ __forceinline__ float hlo(uint32_t v) { return __half2float(__ushort_as_half((unsigned short)(v & 0xffff))); }
__device__ __forceinline__ float hhi(uint32_t v) { return __half2float(__ushort_as_half((unsigned short)(v >> 16))); }
__device__ __forceinline__ float2 h2f(uint32_t v) {
  float2 r;
  asm("{.reg .b16 l, h; mov.b32 {l, h}, %2; cvt.f32.f16 %0, l; cvt.f32.f16 %1, h;}" : "=f"(r.x), "=f"(r.y) : "r"(v));
  return r;
}
__device__ __forceinline__ uint32_t hadd2(uint32_t a, uint32_t b) { uint32_t r; asm("add.rn.f16x2 %0, %1, %2;" : "=r"(r) : "r"(a), "r"(b)); return r; }
__device__ __forceinline__ uint32_t bfma2(uint32_t a, uint32_t b, uint32_t c) { uint32_t r; asm("fma.rn.bf16x2 %0, %1, %2, %3;" : "=r"(r) : "r"(a), "r"(b), "r"(c)); return r; }
__device__ __forceinline__ void center(uint32_t& x, uint32_t m) { asm volatile("add.rn.bf16x2 %0, %0, %1;" : "+r"(x) : "r"(m)); }
__device__ __forceinline__ uint32_t badd2(uint32_t a, uint32_t b) { uint32_t r; asm("add.rn.bf16x2 %0, %1, %2;" : "=r"(r) : "r"(a), "r"(b)); return r; }
__device__ __forceinline__ float round_bf16(float v) { return blo(pack_b2(v, 0.f)); }
__device__ __forceinline__ void ldg64(uint32_t* d, const void* p) { asm volatile("ld.global.cg.v2.u32 {%0,%1}, [%2];" : "=r"(d[0]), "=r"(d[1]) : "l"(p) : "memory"); }
__device__ __forceinline__ uint4 ld_relaxed128(const void* p) { uint4 v; asm volatile("ld.relaxed.gpu.global.v4.u32 {%0,%1,%2,%3}, [%4];" : "=r"(v.x), "=r"(v.y), "=r"(v.z), "=r"(v.w) : "l"(p) : "memory"); return v; }
__device__ __forceinline__ unsigned ld_relaxed(const unsigned* p) { unsigned v; asm volatile("ld.relaxed.gpu.global.u32 %0, [%1];" : "=r"(v) : "l"(p) : "memory"); return v; }
__device__ __forceinline__ void wait_count(const unsigned* p, unsigned target) {
  int it = 0;
  while ((int)(ld_relaxed(p) - target) < 0 && ++it < kSpin) {}
  chaos();
}
__device__ __forceinline__ void wait_count2(const unsigned* p, unsigned target) {
  unsigned a = ld_relaxed(p);
#pragma unroll 1
  for (int it = 0; it < kSpin; it++) {
    __nanosleep(POLL2);
    const unsigned c = ld_relaxed(p);
    if ((int)(a - target) >= 0) break;
    __nanosleep(POLL2);
    a = ld_relaxed(p);
    if ((int)(c - target) >= 0) break;
  }
}
struct cplx { float x, y; };
__device__ __forceinline__ cplx cmul(cplx a, cplx b) { return {fmaf(a.x, b.x, -a.y * b.y), fmaf(a.x, b.y, a.y * b.x)}; }
__device__ __forceinline__ cplx csq(cplx a) { return {fmaf(a.x, a.x, -a.y * a.y), (a.x + a.x) * a.y}; }
__device__ __forceinline__ void pows(cplx* p) {
  p[1] = csq(p[0]); p[2] = cmul(p[1], p[0]); p[3] = csq(p[1]); p[4] = cmul(p[3], p[0]); p[5] = csq(p[2]); p[6] = cmul(p[3], p[2]); p[7] = csq(p[3]);
}
__device__ __forceinline__ uint32_t hcmul(uint32_t a, uint32_t b, uint32_t br) {
  const __half2 ah = *(const __half2*)&a;
  const __half2 r = __hfma2(__low2half2(ah), *(const __half2*)&b, __hmul2(__high2half2(ah), *(const __half2*)&br));
  return *(const uint32_t*)&r;
}
__device__ __forceinline__ float ex2(float x) { float r; asm("ex2.approx.ftz.f32 %0, %1;" : "=f"(r) : "f"(x)); return r; }
__device__ __forceinline__ float rsq(float x) { float r; asm("rsqrt.approx.ftz.f32 %0, %1;" : "=f"(r) : "f"(x)); return r; }
__device__ __forceinline__ float exp_(float x) { return ex2(x * 1.4426950408889634f); }
__device__ __forceinline__ cplx cexp_(float re, float t) {
  t = (t - rintf(t)) * 6.283185307179586f;
  const float e = ex2(re);
  return {e * __cosf(t), e * __sinf(t)};
}

__device__ __forceinline__ void conv_n64i(uint32_t* d, uint32_t a0, uint32_t a1, uint32_t a2, uint32_t a3, uint64_t db) {
  asm volatile("wgmma.mma_async.sync.aligned.m64n64k16.f16.f16.f16 {%0,%1,%2,%3,%4,%5,%6,%7,%8,%9,%10,%11,%12,%13,%14,%15}, {%16,%17,%18,%19}, %20, 0, 1, 1, 0;"
    : "=r"(d[0]),"=r"(d[1]),"=r"(d[2]),"=r"(d[3]),"=r"(d[4]),"=r"(d[5]),"=r"(d[6]),"=r"(d[7]),"=r"(d[8]),"=r"(d[9]),"=r"(d[10]),"=r"(d[11]),"=r"(d[12]),"=r"(d[13]),"=r"(d[14]),"=r"(d[15])
    : "r"(a0), "r"(a1), "r"(a2), "r"(a3), "l"(db));
}
__device__ __forceinline__ void conv_n64(uint32_t* d, uint32_t a0, uint32_t a1, uint32_t a2, uint32_t a3, uint64_t db, int) {
  asm volatile("wgmma.mma_async.sync.aligned.m64n64k16.f16.f16.f16 {%0,%1,%2,%3,%4,%5,%6,%7,%8,%9,%10,%11,%12,%13,%14,%15}, {%16,%17,%18,%19}, %20, 1, 1, 1, 0;"
    : "+r"(d[0]),"+r"(d[1]),"+r"(d[2]),"+r"(d[3]),"+r"(d[4]),"+r"(d[5]),"+r"(d[6]),"+r"(d[7]),"+r"(d[8]),"+r"(d[9]),"+r"(d[10]),"+r"(d[11]),"+r"(d[12]),"+r"(d[13]),"+r"(d[14]),"+r"(d[15])
    : "r"(a0), "r"(a1), "r"(a2), "r"(a3), "l"(db));
}
__device__ __forceinline__ void conv_n32i(uint32_t* d, uint32_t a0, uint32_t a1, uint32_t a2, uint32_t a3, uint64_t db) {
  asm volatile("wgmma.mma_async.sync.aligned.m64n32k16.f16.f16.f16 {%0,%1,%2,%3,%4,%5,%6,%7}, {%8,%9,%10,%11}, %12, 0, 1, 1, 0;"
    : "=r"(d[0]),"=r"(d[1]),"=r"(d[2]),"=r"(d[3]),"=r"(d[4]),"=r"(d[5]),"=r"(d[6]),"=r"(d[7])
    : "r"(a0), "r"(a1), "r"(a2), "r"(a3), "l"(db));
}
__device__ __forceinline__ void conv_n32(uint32_t* d, uint32_t a0, uint32_t a1, uint32_t a2, uint32_t a3, uint64_t db, int) {
  asm volatile("wgmma.mma_async.sync.aligned.m64n32k16.f16.f16.f16 {%0,%1,%2,%3,%4,%5,%6,%7}, {%8,%9,%10,%11}, %12, 1, 1, 1, 0;"
    : "+r"(d[0]),"+r"(d[1]),"+r"(d[2]),"+r"(d[3]),"+r"(d[4]),"+r"(d[5]),"+r"(d[6]),"+r"(d[7])
    : "r"(a0), "r"(a1), "r"(a2), "r"(a3), "l"(db));
}
__device__ __forceinline__ void conv_far(uint32_t* d, uint64_t da, uint64_t db, int) {
  asm volatile("wgmma.mma_async.sync.aligned.m64n64k16.f16.f16.f16 {%0,%1,%2,%3,%4,%5,%6,%7,%8,%9,%10,%11,%12,%13,%14,%15}, %16, %17, 1, 1, 1, 1, 0;"
    : "+r"(d[0]),"+r"(d[1]),"+r"(d[2]),"+r"(d[3]),"+r"(d[4]),"+r"(d[5]),"+r"(d[6]),"+r"(d[7]),"+r"(d[8]),"+r"(d[9]),"+r"(d[10]),"+r"(d[11]),"+r"(d[12]),"+r"(d[13]),"+r"(d[14]),"+r"(d[15])
    : "l"(da), "l"(db));
}
__device__ __forceinline__ void g1_n128i(float* d, uint32_t a0, uint32_t a1, uint32_t a2, uint32_t a3, uint64_t db) {
  asm volatile("wgmma.mma_async.sync.aligned.m64n128k16.f32.bf16.bf16 {%0,%1,%2,%3,%4,%5,%6,%7,%8,%9,%10,%11,%12,%13,%14,%15,%16,%17,%18,%19,%20,%21,%22,%23,%24,%25,%26,%27,%28,%29,%30,%31,%32,%33,%34,%35,%36,%37,%38,%39,%40,%41,%42,%43,%44,%45,%46,%47,%48,%49,%50,%51,%52,%53,%54,%55,%56,%57,%58,%59,%60,%61,%62,%63}, {%64,%65,%66,%67}, %68, 0, 1, 1, 1;"
    : "=f"(d[0]),"=f"(d[1]),"=f"(d[2]),"=f"(d[3]),"=f"(d[4]),"=f"(d[5]),"=f"(d[6]),"=f"(d[7]),"=f"(d[8]),"=f"(d[9]),"=f"(d[10]),"=f"(d[11]),"=f"(d[12]),"=f"(d[13]),"=f"(d[14]),"=f"(d[15]),"=f"(d[16]),"=f"(d[17]),"=f"(d[18]),"=f"(d[19]),"=f"(d[20]),"=f"(d[21]),"=f"(d[22]),"=f"(d[23]),"=f"(d[24]),"=f"(d[25]),"=f"(d[26]),"=f"(d[27]),"=f"(d[28]),"=f"(d[29]),"=f"(d[30]),"=f"(d[31]),"=f"(d[32]),"=f"(d[33]),"=f"(d[34]),"=f"(d[35]),"=f"(d[36]),"=f"(d[37]),"=f"(d[38]),"=f"(d[39]),"=f"(d[40]),"=f"(d[41]),"=f"(d[42]),"=f"(d[43]),"=f"(d[44]),"=f"(d[45]),"=f"(d[46]),"=f"(d[47]),"=f"(d[48]),"=f"(d[49]),"=f"(d[50]),"=f"(d[51]),"=f"(d[52]),"=f"(d[53]),"=f"(d[54]),"=f"(d[55]),"=f"(d[56]),"=f"(d[57]),"=f"(d[58]),"=f"(d[59]),"=f"(d[60]),"=f"(d[61]),"=f"(d[62]),"=f"(d[63])
    : "r"(a0), "r"(a1), "r"(a2), "r"(a3), "l"(db));
}
__device__ __forceinline__ void g1_n128(float* d, uint32_t a0, uint32_t a1, uint32_t a2, uint32_t a3, uint64_t db, int sc) {
  asm volatile("{.reg .pred p; setp.ne.b32 p, %69, 0;\n"
    "wgmma.mma_async.sync.aligned.m64n128k16.f32.bf16.bf16 {%0,%1,%2,%3,%4,%5,%6,%7,%8,%9,%10,%11,%12,%13,%14,%15,%16,%17,%18,%19,%20,%21,%22,%23,%24,%25,%26,%27,%28,%29,%30,%31,%32,%33,%34,%35,%36,%37,%38,%39,%40,%41,%42,%43,%44,%45,%46,%47,%48,%49,%50,%51,%52,%53,%54,%55,%56,%57,%58,%59,%60,%61,%62,%63}, {%64,%65,%66,%67}, %68, p, 1, 1, 1;}"
    : "+f"(d[0]),"+f"(d[1]),"+f"(d[2]),"+f"(d[3]),"+f"(d[4]),"+f"(d[5]),"+f"(d[6]),"+f"(d[7]),"+f"(d[8]),"+f"(d[9]),"+f"(d[10]),"+f"(d[11]),"+f"(d[12]),"+f"(d[13]),"+f"(d[14]),"+f"(d[15]),"+f"(d[16]),"+f"(d[17]),"+f"(d[18]),"+f"(d[19]),"+f"(d[20]),"+f"(d[21]),"+f"(d[22]),"+f"(d[23]),"+f"(d[24]),"+f"(d[25]),"+f"(d[26]),"+f"(d[27]),"+f"(d[28]),"+f"(d[29]),"+f"(d[30]),"+f"(d[31]),"+f"(d[32]),"+f"(d[33]),"+f"(d[34]),"+f"(d[35]),"+f"(d[36]),"+f"(d[37]),"+f"(d[38]),"+f"(d[39]),"+f"(d[40]),"+f"(d[41]),"+f"(d[42]),"+f"(d[43]),"+f"(d[44]),"+f"(d[45]),"+f"(d[46]),"+f"(d[47]),"+f"(d[48]),"+f"(d[49]),"+f"(d[50]),"+f"(d[51]),"+f"(d[52]),"+f"(d[53]),"+f"(d[54]),"+f"(d[55]),"+f"(d[56]),"+f"(d[57]),"+f"(d[58]),"+f"(d[59]),"+f"(d[60]),"+f"(d[61]),"+f"(d[62]),"+f"(d[63])
    : "r"(a0), "r"(a1), "r"(a2), "r"(a3), "l"(db), "r"(sc));
}
__device__ __forceinline__ void g1_n96i(float* d, uint32_t a0, uint32_t a1, uint32_t a2, uint32_t a3, uint64_t db) {
  asm volatile("wgmma.mma_async.sync.aligned.m64n96k16.f32.bf16.bf16 {%0,%1,%2,%3,%4,%5,%6,%7,%8,%9,%10,%11,%12,%13,%14,%15,%16,%17,%18,%19,%20,%21,%22,%23,%24,%25,%26,%27,%28,%29,%30,%31,%32,%33,%34,%35,%36,%37,%38,%39,%40,%41,%42,%43,%44,%45,%46,%47}, {%48,%49,%50,%51}, %52, 0, 1, 1, 1;"
    : "=f"(d[0]),"=f"(d[1]),"=f"(d[2]),"=f"(d[3]),"=f"(d[4]),"=f"(d[5]),"=f"(d[6]),"=f"(d[7]),"=f"(d[8]),"=f"(d[9]),"=f"(d[10]),"=f"(d[11]),"=f"(d[12]),"=f"(d[13]),"=f"(d[14]),"=f"(d[15]),"=f"(d[16]),"=f"(d[17]),"=f"(d[18]),"=f"(d[19]),"=f"(d[20]),"=f"(d[21]),"=f"(d[22]),"=f"(d[23]),"=f"(d[24]),"=f"(d[25]),"=f"(d[26]),"=f"(d[27]),"=f"(d[28]),"=f"(d[29]),"=f"(d[30]),"=f"(d[31]),"=f"(d[32]),"=f"(d[33]),"=f"(d[34]),"=f"(d[35]),"=f"(d[36]),"=f"(d[37]),"=f"(d[38]),"=f"(d[39]),"=f"(d[40]),"=f"(d[41]),"=f"(d[42]),"=f"(d[43]),"=f"(d[44]),"=f"(d[45]),"=f"(d[46]),"=f"(d[47])
    : "r"(a0), "r"(a1), "r"(a2), "r"(a3), "l"(db));
}
__device__ __forceinline__ void g1_n96(float* d, uint32_t a0, uint32_t a1, uint32_t a2, uint32_t a3, uint64_t db, int sc) {
  asm volatile("{.reg .pred p; setp.ne.b32 p, %53, 0;\n"
    "wgmma.mma_async.sync.aligned.m64n96k16.f32.bf16.bf16 {%0,%1,%2,%3,%4,%5,%6,%7,%8,%9,%10,%11,%12,%13,%14,%15,%16,%17,%18,%19,%20,%21,%22,%23,%24,%25,%26,%27,%28,%29,%30,%31,%32,%33,%34,%35,%36,%37,%38,%39,%40,%41,%42,%43,%44,%45,%46,%47}, {%48,%49,%50,%51}, %52, p, 1, 1, 1;}"
    : "+f"(d[0]),"+f"(d[1]),"+f"(d[2]),"+f"(d[3]),"+f"(d[4]),"+f"(d[5]),"+f"(d[6]),"+f"(d[7]),"+f"(d[8]),"+f"(d[9]),"+f"(d[10]),"+f"(d[11]),"+f"(d[12]),"+f"(d[13]),"+f"(d[14]),"+f"(d[15]),"+f"(d[16]),"+f"(d[17]),"+f"(d[18]),"+f"(d[19]),"+f"(d[20]),"+f"(d[21]),"+f"(d[22]),"+f"(d[23]),"+f"(d[24]),"+f"(d[25]),"+f"(d[26]),"+f"(d[27]),"+f"(d[28]),"+f"(d[29]),"+f"(d[30]),"+f"(d[31]),"+f"(d[32]),"+f"(d[33]),"+f"(d[34]),"+f"(d[35]),"+f"(d[36]),"+f"(d[37]),"+f"(d[38]),"+f"(d[39]),"+f"(d[40]),"+f"(d[41]),"+f"(d[42]),"+f"(d[43]),"+f"(d[44]),"+f"(d[45]),"+f"(d[46]),"+f"(d[47])
    : "r"(a0), "r"(a1), "r"(a2), "r"(a3), "l"(db), "r"(sc));
}
__device__ __forceinline__ void g2_n128(float* d, uint64_t da, uint64_t db, int sc) {
  asm volatile("{.reg .pred p; setp.ne.b32 p, %66, 0;\n"
    "wgmma.mma_async.sync.aligned.m64n128k16.f32.bf16.bf16 {%0,%1,%2,%3,%4,%5,%6,%7,%8,%9,%10,%11,%12,%13,%14,%15,%16,%17,%18,%19,%20,%21,%22,%23,%24,%25,%26,%27,%28,%29,%30,%31,%32,%33,%34,%35,%36,%37,%38,%39,%40,%41,%42,%43,%44,%45,%46,%47,%48,%49,%50,%51,%52,%53,%54,%55,%56,%57,%58,%59,%60,%61,%62,%63}, %64, %65, p, 1, 1, 1, 0;}"
    : "+f"(d[0]),"+f"(d[1]),"+f"(d[2]),"+f"(d[3]),"+f"(d[4]),"+f"(d[5]),"+f"(d[6]),"+f"(d[7]),"+f"(d[8]),"+f"(d[9]),"+f"(d[10]),"+f"(d[11]),"+f"(d[12]),"+f"(d[13]),"+f"(d[14]),"+f"(d[15]),"+f"(d[16]),"+f"(d[17]),"+f"(d[18]),"+f"(d[19]),"+f"(d[20]),"+f"(d[21]),"+f"(d[22]),"+f"(d[23]),"+f"(d[24]),"+f"(d[25]),"+f"(d[26]),"+f"(d[27]),"+f"(d[28]),"+f"(d[29]),"+f"(d[30]),"+f"(d[31]),"+f"(d[32]),"+f"(d[33]),"+f"(d[34]),"+f"(d[35]),"+f"(d[36]),"+f"(d[37]),"+f"(d[38]),"+f"(d[39]),"+f"(d[40]),"+f"(d[41]),"+f"(d[42]),"+f"(d[43]),"+f"(d[44]),"+f"(d[45]),"+f"(d[46]),"+f"(d[47]),"+f"(d[48]),"+f"(d[49]),"+f"(d[50]),"+f"(d[51]),"+f"(d[52]),"+f"(d[53]),"+f"(d[54]),"+f"(d[55]),"+f"(d[56]),"+f"(d[57]),"+f"(d[58]),"+f"(d[59]),"+f"(d[60]),"+f"(d[61]),"+f"(d[62]),"+f"(d[63])
    : "l"(da), "l"(db), "r"(sc));
}

constexpr int T_TAB = 8192, T_FAR = 13280, T_EDGE = 16352, T_ZERO = 16368;
constexpr int pos_index(int i) {
  if (i <= 256) return i;
  const int s = i >= 1024 ? 3 : i >= 512 ? 2 : 1;
  return 128 * s + ((i + (1 << (s - 1)) - 1 + ((i >> s) & 1)) >> s);
}
struct TapTable {
  uint32_t v[8][14][12];
  constexpr TapTable() : v() {
    for (int w = 0; w < 8; w++)
      for (int d = 0; d < 14; d++)
        for (int k = 0; k < 12; k++) {
          const int i = 512 * (k >> 2) + 128 * (w & 3) + 8 * ((k & 3) - 1) + d - 6;
          v[w][d][k] = sb + SM_PART + (w >> 2) * 32768 +
                       (i > 1029 ? T_ZERO : i == 1029 ? T_EDGE : T_TAB + (pos_index(i) + 15) * 8 + (pos_index(i) == pos_index(i - 1) ? 4 : 0));
        }
  }
};
__device__ __align__(16) const TapTable g_taps = TapTable();

template <int G> __device__ __forceinline__ void load_taps(uint32_t* q, uint32_t tb, const uint32_t* ad, uint32_t st0) {
  uint32_t r[17];
  if (G == 0) {
    r[0] = lds32(tb + ad[0]); r[1] = lds32(tb + ad[1]);
#pragma unroll
    for (int m = 2; m < 17; m++) r[m] = lds32(tb + ad[2 + (m & 1)] + ((m - 2) >> 1) * st0);
  } else {
    r[0] = lds32(tb + ad[4 * G]); r[1] = lds32(tb + ad[4 * G + 1]);
#pragma unroll
    for (int m = 2; m < 17; m++) r[m] = lds32(tb + ad[4 * G + 2 + (m & 1)] + ((m - 2) >> 1) * 32);
  }
  q[2] = r[0];
#pragma unroll
  for (int s = 0; s < 8; s++) { q[4 * s] = r[2 * s + 1]; q[4 * s + 1] = r[2 * s + 2]; }
}
__device__ __forceinline__ void expand_taps(uint32_t* q) {
#pragma unroll
  for (int s = 0; s < 8; s++) {
    if (s) asm volatile("xor.b32 %0, %1, %2;" : "=r"(q[4 * s + 2]) : "r"(q[4 * s - 3]), "r"(blockIdx.y));
    asm volatile("xor.b32 %0, %1, %2;" : "=r"(q[4 * s + 3]) : "r"(q[4 * s]), "r"(blockIdx.y));
  }
}
__device__ __forceinline__ void sched_fence() {
  asm volatile("{.reg .u32 t; mov.u32 t, %%clock; st.shared.u32 [%0], t;}" ::"r"(sb + SM_MISC + 4) : "memory");
}
template <bool INIT> __device__ __forceinline__ void conv64(uint32_t* acc, const uint32_t* q, uint64_t vd) {
#pragma unroll
  for (int s = 7; s >= 0; s--) {
    if (INIT && s == 7) conv_n64i(acc, q[28], q[29], q[30], q[31], vd - 7);
    else conv_n64(acc, q[4 * s], q[4 * s + 1], q[4 * s + 2], q[4 * s + 3], vd - s, 1);
  }
}
__device__ __forceinline__ void conv32(uint32_t* acc, const uint32_t* q, uint64_t vd) {
#pragma unroll
  for (int s = 0; s < 8; s++) {
    if (s == 0) conv_n32i(acc, q[0], q[1], q[2], q[3], vd);
    else conv_n32(acc, q[4 * s], q[4 * s + 1], q[4 * s + 2], q[4 * s + 3], vd - s, 1);
  }
}
__device__ __forceinline__ void store_partial(const uint32_t* acc, uint32_t pa) {
#pragma unroll
  for (int J = 0; J < 8; J += 2) stsm4t(pa + J * 128, acc[2 * J], acc[2 * J + 1], acc[2 * J + 2], acc[2 * J + 3]);
}

__device__ __forceinline__ void far_taps(int wg, int t) {
  const int u = t & 63;
  const uint32_t ks = sb + SM_KG + wg * 32768 + (t >> 6) * 16384 + 1040 + u * 4;
  uint32_t k[8];
#pragma unroll
  for (int i = 0; i < 8; i++) {
    k[i] = hadd2(lds32(ks - i * 4), lds32(ks + 8192 - i * 4));
    if (u < i) k[i] = 0;
  }
  const uint32_t r = sb + SM_PART + wg * 32768 + (t >> 6) * 16384 + T_FAR;
  sts128(r + 512 + u * 16, __byte_perm(k[0], k[1], 0x5410), __byte_perm(k[2], k[3], 0x5410), __byte_perm(k[4], k[5], 0x5410), __byte_perm(k[6], k[7], 0x5410));
  sts128(r + 2048 + u * 16, __byte_perm(k[0], k[1], 0x7632), __byte_perm(k[2], k[3], 0x7632), __byte_perm(k[4], k[5], 0x7632), __byte_perm(k[6], k[7], 0x7632));
}
__device__ __forceinline__ void far_windows(int wg, int t0) {
  const uint32_t tb = sb + SM_PART + wg * 32768;
#pragma unroll 1
  for (int it = t0; it < 256; it += 32 * NWW) {
    const int c = it >> 7, t = it & 127, a = (t & 7) + 8 * (t >> 4), h = (t >> 3) & 1;
    const uint32_t vb = sb + SM_V + (4 * wg + 2 * c) * V_PITCH;
    const uint32_t own = vb + h * V_PITCH + (8 + a) * 16, oth = vb + (h ^ 1) * V_PITCH + (7 + a + h) * 16;
    const uint2 b3 = lds64(oth - 8), b0 = lds64(own);
    const uint4 b2 = lds128(own - 16), b1 = lds128(oth);
    const uint32_t p[12] = {b3.x, b3.y, b2.x, b2.y, b2.z, b2.w, b1.x, b1.y, b1.z, b1.w, b0.x, b0.y};
    uint32_t q[11], s1[11], s2[10], e[4], o[4];
#pragma unroll
    for (int i = 0; i < 11; i++) { q[i] = __byte_perm(p[i], p[i + 1], 0x5432); s1[i] = hadd2(p[i], q[i]); }
#pragma unroll
    for (int i = 0; i < 10; i++) s2[i] = hadd2(s1[i], s1[i + 1]);
#pragma unroll
    for (int i = 0; i < 4; i++) { e[i] = hadd2(hadd2(s2[i], p[i + 4]), s2[i + 2]); o[i] = hadd2(hadd2(q[i + 4], s1[i + 5]), s2[i + 6]); }
    const uint32_t d = tb + c * 16384 + T_TAB + t * 16;
    sts128(d, o[0], o[1], o[2], o[3]);
    sts128(d + 2048, e[0], e[1], e[2], e[3]);
  }
}
__device__ __forceinline__ void edge_load(uint32_t* q, uint32_t o, const uint32_t* ad) {
  q[2] = lds32(o + ad[8]); q[0] = lds32(o + ad[9]); q[1] = lds32(o + ad[10]);
  asm volatile("xor.b32 %0, %5, %7; xor.b32 %1, %6, %7; and.b32 %2, %5, %7; and.b32 %3, %6, %7; min.u32 %4, %6, %7;"
               : "=r"(q[3]), "=r"(q[6]), "=r"(q[4]), "=r"(q[5]), "=r"(q[7]) : "r"(q[0]), "r"(q[1]), "r"(blockIdx.y));
}
__device__ __forceinline__ void far_mma(uint32_t* acc, const uint32_t* q, uint64_t vd, uint64_t wd, uint64_t rd) {
  conv_n64(acc, q[0], q[1], q[2], q[3], vd, 1);
  conv_n64(acc, q[4], q[5], q[6], q[7], vd - 1, 1);
  conv_far(acc, wd, rd + 32, 1);
  conv_far(acc, wd + 64, rd, 1);
}
template <int HF, int C0, int C1> __device__ __forceinline__ void finish_h(int wg, int t) {
  const uint32_t xa = sb + SM_XS + HF * XS_STEP + wg * 4096 + t * 16, tb = sb + SM_PART + wg * 32768;
  const uint32_t base = tb + (t & 8) * 128 + (t >> 4) * 128 + (t & 7) * 16;
  const uint2 fu = lds64(sb + SM_MISC + 16 + wg * 8);
  uint4 p[2][4], xv[2];
#pragma unroll
  for (int s = 0; s < 4; s++) {
    const uint32_t a = t >= 16 * s ? base + HF * 8192 : HF ? base + 1024 : tb + T_ZERO - s * 1920;
#pragma unroll
    for (int c = C0; c < C1; c++) p[c][s] = lds128(a + s * 1920 + c * 16384);
  }
#pragma unroll
  for (int c = C0; c < C1; c++) xv[c] = lds128(xa + c * 2048);
#pragma unroll
  for (int c = C0; c < C1; c++) {
    const uint32_t f = c ? fu.y : fu.x;
    const float2 y0 = h2f(hadd2(hadd2(p[c][0].x, p[c][1].x), hadd2(p[c][2].x, p[c][3].x))), y1 = h2f(hadd2(hadd2(p[c][0].y, p[c][1].y), hadd2(p[c][2].y, p[c][3].y)));
    const float2 y2 = h2f(hadd2(hadd2(p[c][0].z, p[c][1].z), hadd2(p[c][2].z, p[c][3].z))), y3 = h2f(hadd2(hadd2(p[c][0].w, p[c][1].w), hadd2(p[c][2].w, p[c][3].w)));
    const float g = bhi(f);
    sts128(xa + c * 2048, pack_b2(fmaf(g, y0.x, blo(xv[c].x)), fmaf(g, y0.y, bhi(xv[c].x))), pack_b2(fmaf(g, y1.x, blo(xv[c].y)), fmaf(g, y1.y, bhi(xv[c].y))),
           pack_b2(fmaf(g, y2.x, blo(xv[c].z)), fmaf(g, y2.y, bhi(xv[c].z))), pack_b2(fmaf(g, y3.x, blo(xv[c].w)), fmaf(g, y3.y, bhi(xv[c].w))));
  }
}

struct RowC { float k0, k1, k2; };
__device__ __forceinline__ float after(float v, float dep, uint32_t zero) { return __uint_as_float(__float_as_uint(v) | (__float_as_uint(dep) & zero)); }
template <int NB, int PC> __device__ __forceinline__ void epilogue1(const float* acc, uint32_t sta, const RowC& c0, const RowC& c1) {
  const uint32_t zero = blockIdx.y;
  float t0 = 0.f, t1 = 0.f, dep = 0.f;
  uint32_t r[4];
#pragma unroll
  for (int i = 0; i <= 2 * NB; i++) {
    float n0, n1;
    if (i < 2 * NB) {
      const RowC& c = (i & 1) ? c1 : c0;
      const float g0 = acc[2 * i], g1 = acc[2 * i + 1], k1 = PC ? after(c.k1, dep, zero) : c.k1;
      const float z0 = g0 * fmaf(k1 * g0, g0, c.k0), z1 = g1 * fmaf(k1 * g1, g1, c.k0);
      asm("tanh.approx.f32 %0, %1;" : "=f"(n0) : "f"(z0));
      asm("tanh.approx.f32 %0, %1;" : "=f"(n1) : "f"(z1));
      dep = z1;
    }
    if (i > 0) {
      const int j = i - 1;
      const float k2 = PC ? after(((j & 1) ? c1 : c0).k2, dep, zero) : ((j & 1) ? c1 : c0).k2;
      const float h0 = fmaf(t0, k2, k2) * acc[2 * j] * acc[4 * NB + 2 * j], h1 = fmaf(t1, k2, k2) * acc[2 * j + 1] * acc[4 * NB + 2 * j + 1];
      r[j & 3] = pack_b2(h0, h1);
      dep = h0;
      if ((j & 3) == 3) stsm4(sta + (j >> 2) * 256, r[0], r[1], r[2], r[3]);
    }
    t0 = n0; t1 = n1;
  }
}

__device__ __forceinline__ void gemm1_stage(float* acc, const uint32_t* a, int n, bool first PROF_ARG) {
  const int slot = n < 10 ? n : n - 10;
  mbar_wait_data(bars + 8 * (B_FULL1 + n % 12), n >= 12);
  PROF2(32 + n);
  const uint64_t db = mkdesc(sb + SM_RING + slot * 16384, 8192, 1024, 1);
  wg_fence();
#pragma unroll
  for (int k = 0; k < 4; k++) {
    if (first && k == 0) g1_n128i(acc, a[0], a[1], a[2], a[3], db);
    else g1_n128(acc, a[4 * k], a[4 * k + 1], a[4 * k + 2], a[4 * k + 3], db + k * 128, 1);
  }
  wg_commit();
}
template <int KS> __device__ __forceinline__ void gemm2_stage(float* acc, int n, int lane PROF_ARG) {
  const int s = n & 7;
  mbar_wait_data(bars + 8 * (B_FULL2 + s), (n >> 3) & 1);
  PROF2(64 + n);
  const uint32_t base = sb + SM_RING + s * 24576;
  const uint64_t da = mkdesc(base + 16384, 8192, 1024, 1), db = mkdesc(base, 128, KS == 4 ? 1024 : 768, 0);
  wg_fence();
#pragma unroll
  for (int k = 0; k < KS; k++) g2_n128(acc, da + 128 * k, db + 16 * k, k ? 1 : n);
  wg_commit();
  wg_wait<1>();
  if (n > 0 && n <= 16 && lane == 0) mbar_arrive(bars + 8 * (B_EMPTY2 + n - 1));
}

template <int NJ> __device__ __forceinline__ void store_out(const float* acc, const uint32_t* res, uint32_t oa) {
#pragma unroll
  for (int J = 0; J < NJ; J += 2) {
    const float* d = acc + 4 * J;
    const uint32_t* r = res + 2 * J;
    stsm4t(oa + J * 1024, badd2(pack_b2(d[0], d[1]), r[0]), badd2(pack_b2(d[2], d[3]), r[1]), badd2(pack_b2(d[4], d[5]), r[2]), badd2(pack_b2(d[6], d[7]), r[3]));
  }
  fence_async();
}

__device__ __forceinline__ void load_w(int n, int s, int f, int tj, const CUtensorMap* mg, const CUtensorMap* mu) {
  const uint32_t fb = sb + SM_BAR + 8 * (B_FULL1 + f), dst = sb + SM_RING + s * 16384;
  mbar_expect(fb, 16384);
  tma2d(dst, mg, 176 * tj + 64 * (n >> 3), 64 * ((n ^ tj) & 7), fb);
  tma2d(dst + 8192, mu, 176 * tj + 64 * (n >> 3), 64 * ((n ^ tj) & 7), fb);
}

__device__ __forceinline__ void load_wd(int n, int ti, int tj, const CUtensorMap* md, const CUtensorMap* md48, const CUtensorMap* mr) {
  const int s = n & 7, p = n >> 3;
  mbar_wait(bars + 8 * (n < 8 ? B_EMPTY1 + ((0xB9753200u >> (4 * n)) & 15) : B_EMPTY2 + n - 8), n < 8);
  const uint32_t fb = bars + 8 * (B_FULL2 + s);
  if (elect()) {
    mbar_expect(fb, n == 0 ? 40960 : p < 2 ? 24576 : 18432);
    tma2d(sb + SM_RING + s * 24576 + 16384, p < 2 ? md : md48, 64 * tj, 176 * s + 64 * p, fb);
    if (n == 0) {
      tma2d(sb + SM_OST, mr, 64 * ti, 64 * tj, fb);
      tma2d(sb + SM_OST + 8192, mr, 64 * ti, 512 + 64 * tj, fb);
    }
  }
}
__device__ __forceinline__ void load_h(int n, const uint4* H) {
  if (elect()) bulk_g2s(sb + SM_RING + (n & 7) * 24576, H + n * 1024, n < 16 ? 16384 : 12288, bars + 8 * (B_FULL2 + (n & 7)));
}

struct Params {
  const uint32_t *x, *lar, *aim, *cre, *cim;
  const uint32_t *ldt, *dsk;
  Scratch* scratch;
  const void* taps;
  const uint4 *wg, *wu, *wd;
};

__global__ void __launch_bounds__(kThreads, 1)
fused_kernel(const Params P, const __grid_constant__ CUtensorMap mg, const __grid_constant__ CUtensorMap mu,
             const __grid_constant__ CUtensorMap md, const __grid_constant__ CUtensorMap md48,
             const __grid_constant__ CUtensorMap mx, const __grid_constant__ CUtensorMap mh, const __grid_constant__ CUtensorMap mr,
             const __grid_constant__ CUtensorMap mo, const __grid_constant__ CUtensorMap mg8, const __grid_constant__ CUtensorMap mu8) {
  extern __shared__ __align__(1024) uint8_t smem[];
  const int tid = threadIdx.x, lane = tid & 31, warp = __shfl_sync(0xffffffffu, tid >> 5, 0), b = blockIdx.x;
  const int ti = (b & 3) + 4 * (b >> 5), tj = (b >> 2) & 7;
  const int ui = b >> 3, uj = b & 7;
  const unsigned t_start = clock();
  PROFT(0);
  const int chn = 4 * b + (tid >> 6);
  uint32_t p_lar, p_aim, p_cre, p_cim, o_cre, o_cim, p_ldt, p_dsk;
  if (tid < 256 && b < kCtas) {
    const int po = b * 256 + tid;
    p_lar = __ldg(P.lar + po); p_aim = __ldg(P.aim + po); p_cre = __ldg(P.cre + po); p_cim = __ldg(P.cim + po);
    o_cre = __ldg(P.cre + (po ^ 32)); o_cim = __ldg(P.cim + (po ^ 32));
    p_ldt = __ldg(P.ldt + (chn >> 1)); p_dsk = __ldg(P.dsk + (chn >> 1));
  }
  Scratch* const S = P.scratch;
  if (((uint32_t)__cvta_generic_to_shared(smem) & 0xffffff) != sb) return;

  if (b >= kCtas) {
    if (tid == 0) {
#pragma unroll 1
      for (int i = 0; i < 12; i++) { mbar_init(bars + 8 * (B_FULL1 + i), 1); mbar_init(bars + 8 * (B_EMPTY1 + i), 4); }
      fence_async();
    }
    while ((unsigned)clock() - t_start < DCS) {}
    __syncthreads();
    const int g = warp < 8 ? warp >> 2 : warp & 1, j = 2 * (b - kCtas) + g;
    int slot = 6 * g, ph = 0;
    if (warp < 8) {
#pragma unroll 1
      for (int p = 0; p < SPP; p++) {
        float acc[64];
#pragma unroll
        for (int i = 0; i < 64; i++) acc[i] = 0.f;
#pragma unroll 1
        for (int st = 0; st < 8; st++) {
          mbar_wait(bars + 8 * (B_FULL1 + slot), ph);
          const uint64_t db = mkdesc(sb + SM_RING + slot * 16384, 8192, 1024, 1);
          uint32_t one = 0x3f803f80u | blockIdx.y;
          wg_fence();
#pragma unroll
          for (int k = 0; k < 4; k++) g1_n128(acc, one, one, one, one, db + k * 128, 1);
          wg_commit();
          wg_wait<0>();
          if (lane == 0) mbar_arrive(bars + 8 * (B_EMPTY1 + slot));
          if (++slot == 6 * g + 6) { slot -= 6; ph ^= 1; }
        }
        if ((warp & 3) == 0) {
          if (lane < 4) {
#pragma unroll
            for (int J = 0; J < 8; J++) S->cs[(j * 24 + p * 8 + J) * 4 + lane] = make_float4(acc[4 * J], acc[4 * J + 1], acc[32 + 4 * J], acc[33 + 4 * J]);
          }
          __threadfence();
          __syncwarp();
          if (lane == 0) asm volatile("red.relaxed.gpu.global.add.u32 [%0], 128;" ::"l"(&S->cnt[(C_CS + j * 3 + p) * 32]) : "memory");
        }
        PROFV(1 + p, 0);
      }
    } else if (warp < 10) {
#pragma unroll 1
      for (int n = 0; n < 8 * SPP; n++) {
        mbar_wait(bars + 8 * (B_EMPTY1 + slot), ph ^ 1);
        if (elect()) load_w(n, slot, slot, j, &mg, &mu);
        if (++slot == 6 * g + 6) { slot -= 6; ph ^= 1; }
      }
    }
  } else if (warp >= 8) {
    const int ht = tid - 256, hw = warp - 8;
    if (lane == 0) {
#pragma unroll
      for (int i = 0; i < B_NUM; i += 4) mbar_init(bars + 8 * (i + hw), i < B_EMPTY1 ? 1 : i < B_EMPTY2 ? 8 : 4);
    }
    __syncwarp();
    unsigned target;
    asm volatile("ld.relaxed.gpu.global.u32 %0, [%1];" : "=r"(target) : "l"(&S->cnt[C_LO * 32]) : "memory");
    uint4 xl[8];
    {
      const uint4* src = (const uint4*)P.x + (128 * ui + 32 * hw + 2 * (lane & 8) + 2 * uj + ((lane >> 2) & 1)) * 64 + 2 * (lane & 16) + (lane & 3);
#pragma unroll
      for (int m = 0; m < 8; m++)
        asm volatile("ld.global.nc" XH ".v4.u32 {%0,%1,%2,%3}, [%4];" : "=r"(xl[m].x), "=r"(xl[m].y), "=r"(xl[m].z), "=r"(xl[m].w) : "l"(src + 4 * m) : "memory");
    }
    PROF(19);
    if (lane == 0) {
      asm volatile("prefetch.tensormap [%0];" ::"l"(hw == 0 ? &mx : hw == 1 ? &mg : hw == 2 ? &mu : &mh) : "memory");
    }
    sts64(sb + SM_V + (ht >> 4) * V_PITCH + (ht & 15) * 8, 0, 0);
    if (lane != 15 && lane < 18) sts64(sb + SM_PART + hw * 16384 + (lane < 16 ? T_TAB : T_ZERO - 128) + lane * 8, 0, 0);
    sts128(sb + SM_PART + hw * 16384 + T_FAR + lane * 16, 0, 0, 0, 0);
    sts128(sb + SM_PART + hw * 16384 + T_FAR + 1536 + lane * 16, 0, 0, 0, 0);
    PROF(16);
    uint4 xr[8];
#pragma unroll
    for (int m = 0; m < 8; m++) xr[m] = make_uint4(0, 0, 0, 0);
#pragma unroll 1
    for (int real = !HDRY; real < 2; real++) {
      if (real) {
#pragma unroll
        for (int m = 0; m < 8; m++) {
          asm volatile("" : "+r"(xl[m].x), "+r"(xl[m].y), "+r"(xl[m].z), "+r"(xl[m].w));
          xr[m] = xl[m];
        }
        target += 128;
        sts32(sb + SM_MISC, target);
      }
      const int j = 2 * hw + ((lane >> 3) & 1), q2 = 2 * (lane & 3);
      const uint32_t xt = sb + SM_XT + (4 * (lane & 16) + q2) * 128 + 2 * (lane & 4), inv = (lane & 4) ? 0u : ~0u;
#pragma unroll
      for (int m = 0; m < 8; m++) {
        sts64(xt + m * 1024 + (j ^ q2) * 16, xr[m].x ^ inv, xr[m].y);
        sts64(xt + m * 1024 + 128 + (j ^ q2 ^ 1) * 16, xr[m].z ^ inv, xr[m].w);
      }
      PROF(17);
      if (real) fence_async();
      bar_sync(2, 128);
      if (ht == 96 && real) {
        asm volatile("cp.async.bulk.tensor.2d.global.shared::cta.bulk_group [%0, {%2, %3}], [%1];" ::"l"(&mx), "r"(sb + SM_XT), "r"(64 * b), "r"(0) : "memory");
        bulk_s2g(S->st2 + (ti * 8 + tj) * 64, sb + SM_PART + T_FAR, 512);
        bulk_s2g(S->st2 + (ti * 8 + tj) * 64 + 32, sb + SM_PART + T_FAR, 512);
      }
      PROF(20);
      float sa[4][4];
#pragma unroll
      for (int m = 0; m < 4; m++) sa[m][0] = sa[m][1] = sa[m][2] = sa[m][3] = 0.f;
#pragma unroll
      for (int m = 0; m < 8; m++) {
        mma_bf16(sa[(2 * m) & 3], xr[m].x, 0x3f803f80u, xr[m].y, 0x3f803f80u, xr[m].x, xr[m].y);
        mma_bf16(sa[(2 * m + 1) & 3], xr[m].z, 0x3f803f80u, xr[m].w, 0x3f803f80u, xr[m].z, xr[m].w);
      }
      const bool odd = lane & 4;
      float sq = odd ? (sa[0][1] + sa[1][1]) + (sa[2][1] + sa[3][1]) : (sa[0][0] + sa[1][0]) + (sa[2][0] + sa[3][0]);
      float sm = odd ? (sa[0][3] + sa[1][3]) + (sa[2][3] + sa[3][3]) : (sa[0][2] + sa[1][2]) + (sa[2][2] + sa[3][2]);
      sq += __shfl_xor_sync(0xffffffffu, sq, 18);
      sm += __shfl_xor_sync(0xffffffffu, sm, 18);
      const float m = sm * (1.f / kD);
      const float r = rsq(fmaxf(sq * (1.f / kD) - m * m, 0.f) + 1e-5f) * (1.f / 32.f);
      if (real && lane < 16 && (lane & 3) == (lane >> 3))
        asm volatile("st.relaxed.gpu.global.v2.u32 [%0], {%1,%2};" ::"l"((uint2*)(S->stats + 8 * b + 2 * hw) + (lane >> 2)), "r"(__float_as_uint(-m * r)), "r"(__float_as_uint(r) | 1u) : "memory");
    }
    PROF(1);
    asm volatile("setmaxnreg.dec.sync.aligned.u32 " RH ";");
    asm volatile("cp.async.bulk.wait_group.read 0;" ::: "memory");
#pragma unroll 1
    for (int g = 0; g < 2; g++) {
      bar_sync(12 + g, 256);
      far_taps(g, ht);
    }
    bar_sync(2, 128);
    if (hw == 3) {
      mbar_wait(bars + 8 * (B_V + WV), 0);
      if (lane == 0) {
        mbar_expect(bars + 8 * B_WS, 6144);
        asm volatile("cp.async.bulk.tensor.3d.shared::cluster.global.mbarrier::complete_tx::bytes [%0], [%1, {%3, %4, %5}], [%2];" ::"r"(sb + SM_WS),
                     "l"((ti & 1) ? &mu8 : &mg8), "r"(bars + 8 * B_WS), "r"(0), "r"(64 * ((ti >> 1) ^ tj)), "r"(22 * tj + 16) : "memory");
#pragma unroll 1
        for (int n = 0; n < 4; n++) load_w(n, n, n, tj, &mg, &mu);
        prefetch_l2(P.wd + b * 688, 11008);
        prefetch_l2(P.wg + b * 688, 11008);
        prefetch_l2(P.wu + b * 688, 11008);
      } else if (lane < 4) {
        mbar_arrive(bars + 8 * B_WS);
      }
      __syncwarp();
      mbar_wait(bars + 8 * B_WS, 0);
      if (lane == 0) {
        bulk_s2g(S->wp + (tj * 16 + ti) * 384, sb + SM_WS, 6144);
      }
      __syncwarp();
    }
    if (hw < NWW) {
#pragma unroll 1
      for (int g = 0; g < 2; g++) {
        if (LATEW && g == 2 - LATEW) bar_sync(8, kThreads);
        else mbar_wait(bars + 8 * (B_V + (g | WST)), 0);
        far_windows(g, ht);
        bar_arrive(12 + g, 128 + 32 * NWW);
      }
    }
    PROF(18);
    if (hw == 0 || hw == 3) {
      if (hw == 0) {
        bar_sync(5, 128);
#pragma unroll 1
        for (int n = 4; n < 8; n++) {
          if (n >= 4 + PW) mbar_wait(bars + 8 * (B_FULL1 + n - PW), 0);
          if (elect()) load_w(n, n, n, tj, &mg, &mu);
        }
      } else {
        if (lane < 8) mbar_expect(bars + 8 * (B_XFULL + lane), 16384);
        bar_sync(8, LATEW ? kThreads : 288);
        if (lane == 0) {
          bulk_s2g(S->h + b * 512, sb + SM_XS, 8192);
          bulk_wait_signal(&S->cnt[C_LO * 32], 1);
        }
        __syncwarp();
#pragma unroll 1
        for (int i = 0; i < 8; i++) {
          const int hf = i >> 2;
          if (hf) mbar_wait(bars + 8 * (B_XFREE - 4 + i), 0);
          if ((i & 3) == 0) {
            PROFV(2 + 2 * hf, 0);
            if (POLL2) wait_count2(&S->cnt[C_LO * 32 + hf * HIOFF], target << hf);
            else wait_count(&S->cnt[C_LO * 32 + hf * HIOFF], target << hf);
            PROFV(3 + 2 * hf, 0);
          }
          if (elect()) tma2d(sb + SM_XST + (i & 3) * 16384, &mh, 64 * ti, 128 * (i ^ (tj >> 1)), bars + 8 * (B_XFULL + i));
          if (i == XW) bar_arrive(5, 128);
        }
      }
#pragma unroll 1
      for (int n = 8 + (hw & 1); n < 24; n += 2) {
        const int m = n - PACE;
        if (m >= 8) mbar_wait(bars + 8 * (B_FULL1 + (m < 12 ? m : m - 12)), m >= 12);
        mbar_wait(bars + 8 * (n < 10 ? B_XFREE - 4 + n : B_EMPTY1 + (n < 16 ? n - 10 : (0xBA998876u >> (4 * n - 64)) & 15)), 0);
        if (elect()) {
          if (n < 16) {
            load_w(n, n < 10 ? n : n - 10, n < 12 ? n : n - 12, tj, &mg, &mu);
          } else {
            mbar_expect(bars + 8 * (B_FULL1 + n - 12), 12288);
            bulk_g2s(sb + SM_RING + (n - 8) * 12288, S->wp + (tj * 8 + n - 16) * 768, 12288, bars + 8 * (B_FULL1 + n - 12));
          }
        }
        PROF2(32 + n);
      }
      mbar_wait(bars + 8 * (B_EMPTY1 + 11), 0);
#pragma unroll 1
      for (int n = hw & 1; n < 12; n += 2) {
        load_wd(n, ui, uj, &md, &md48, &mr);
        if ((n & 7) < 2) mbar_wait(bars + 8 * (B_HRDY + (n >> 3)), 0);
        load_h(n, S->H + ui * 24576);
        PROF2(64 + n);
      }
    } else {
      bar_sync(hw == 1 ? 15 : 9, 160);
      if (lane == 0) bulk_s2g(S->h + 65536 + b * 512 + (hw - 1) * 256, sb + SM_XS + XS_STEP + (hw - 1) * 4096, 4096);
      __syncwarp();
      bar_arrive(5, 128);
      if (lane == 0) bulk_wait_signal(&S->cnt[C_LO * 32 + HIOFF], 1);
      __syncwarp();
      PROF(6);
      const int w = hw - 1;
#pragma unroll 1
      for (int p = 0; p < 3; p++) {
        if (p + w == 0) {
          const int c = p + w;
          wait_count(&S->cnt[(C_CS + tj * 3 + c) * 32], target);
          const float4 v = __ldcg(S->cs + (tj * 3 + c) * 32 + lane);
          if (c < 2 || lane < 24) sts128(sb + SM_CS + c * 512 + lane * 16, __float_as_uint(v.x), __float_as_uint(v.y), __float_as_uint(v.z), __float_as_uint(v.w));
          __syncwarp();
          if (lane < 4) mbar_arrive(bars + 8 * (B_CS + c));
        }
        if (p + w == 3) {
          wait_count(&S->cnt[(C_G2 + ((b + GOFF) & 127) / GS) * 32], target);
          bar_arrive(7, 288);
        }
        mbar_wait(bars + 8 * (B_HFULL + w), p & 1);
        PROF(2);
        if (lane == 0) {
          const uint32_t n = p < 2 ? 8192 : 6144;
          bulk_s2g((const uint8_t*)(S->H + ((ti * 3 + p) * 8 + tj) * 1024) + w * n, sb + SM_HST + w * XS_STEP, n);
          bulk_wait_signal(&S->cnt[(C_H + ti * 3 + p) * 32], 8);
          mbar_arrive(bars + 8 * (B_HEMPTY + w));
        }
        __syncwarp();
        PROF(3);
        if (p == RST - 1 && w == RSTW) {
#pragma unroll 1
          for (int i = 0; i < 32; i++) {
            S->xt[b * 1024 + i * 32 + lane] = make_uint4(0, 0, 0, 0);
            __nanosleep(20);
          }
        }
        if (H3P ? w == (p < 2) : w == 1 && p < 2) {
          wait_count(&S->cnt[(C_H + ui * 3 + p) * 32], target);
          if (p < 2 ? lane == 0 : lane < 4) mbar_arrive(bars + 8 * (p < 2 ? B_HRDY + p : B_WS));
        }
      }
      if (ht < 40) S->stats[8 * b + lane] = make_uint4(0, 0, 0, 0);
    }
  } else {
    const int wg = warp >> 2, w = warp & 3, g = lane >> 2, q = lane & 3;
    uint32_t ad[12];
#pragma unroll
    for (int i = 0; i < 3; i++) {
      const uint4 v = __ldg((const uint4*)P.taps + (warp * 14 + g - 2 * q + 6) * 3 + i);
      ad[4 * i] = v.x; ad[4 * i + 1] = v.y; ad[4 * i + 2] = v.z; ad[4 * i + 3] = v.w;
    }
    const uint32_t st0 = w < 2 ? 128 : 64;
    const uint32_t wa = sb + SM_KG + warp * 8192;
    {
      float kacc[5][4];
#pragma unroll
      for (int j = 0; j < 5; j++)
#pragma unroll
        for (int i = 0; i < 4; i++) kacc[j][i] = 0.f;
      const uint32_t st = wa + (lane >> 3) * 144 + (lane & 7) * 16;
      const uint32_t la = wa + (lane & 15) * 144 + (lane >> 4) * 16, lb = wa + (16 + (lane & 7)) * 144 + (lane >> 3) * 16;
      if (PF) {
        asm volatile("" ::"r"(st), "r"(la), "r"(lb));
        sched_fence();
        asm volatile("" : "+r"(p_lar), "+r"(p_aim), "+r"(p_cre), "+r"(p_cim), "+r"(o_cre), "+r"(o_cim), "+r"(p_ldt), "+r"(p_dsk));
      }
      const float dt = round_bf16(exp_((chn & 1) ? bhi(p_ldt) : blo(p_ldt))), dsk = (chn & 1) ? bhi(p_dsk) : blo(p_dsk);
      PROF(1);
      uint32_t mx = __vmaxu2(__vmaxu2(p_cre & 0x7fff7fffu, p_cim & 0x7fff7fffu), __vmaxu2(o_cre & 0x7fff7fffu, o_cim & 0x7fff7fffu));
      mx = __reduce_max_sync(0xffffffffu, max(mx << 16, mx));
      mx = __float_as_uint(fmaxf(2.f * dt * __uint_as_float(mx), fabsf(dsk) * (1.f / 65536.f))) & 0x7f800000u;
      mx = min(max(mx, 0x01000000u), 0x7a000000u);
      const float is = __uint_as_float(0x7d000000u - mx), inv = 2.f * dt * is;
      sts32(sb + SM_MISC + 16 + (warp >> 1) * 4, __byte_perm(mx + (9 << 23), 0, 0x3232));
      float k0[4] = {0.5f * dsk * is, 0.f, 0.f, 0.f};
      if (PP && wg == 1) bar_sync(7, 256);
#pragma unroll 1
      for (int r = 1; r < 3; r++) {
        const float ar = -1.4426950408889634f * round_bf16(exp_(blo(p_lar))) * dt, ai = 0.15915494309189535f * blo(p_aim) * dt;
        cplx c = {blo(p_cre) * inv, -blo(p_cim) * inv};
        p_lar >>= 16; p_aim >>= 16; p_cre >>= 16; p_cim >>= 16;
        cplx s[8], u[8];
        s[0] = cexp_(ar, ai);
        u[0] = cexp_(128.f * ar, 128.f * ai);
        pows(s);
        pows(u);
        const cplx z8 = {s[7].x, -s[7].y}, z16 = csq(z8), z24 = cmul(z16, z8), z32 = csq(z16);
        __syncwarp();
        {
          const uint32_t y1 = pack_h2(z8.x, z8.y), y1r = pack_h2(-z8.y, z8.x), y2 = pack_h2(z16.x, z16.y), y2r = pack_h2(-z16.y, z16.x);
          const uint32_t y3 = pack_h2(z24.x, z24.y), y3r = pack_h2(-z24.y, z24.x);
#pragma unroll
          for (int k = 0; k < 4; k++) {
            if (k) c = cmul(c, z32);
            const uint32_t ch = pack_h2(c.x, c.y);
            stsm4(st + (4 * k) * 144, ch, hcmul(ch, y1, y1r), hcmul(ch, y2, y2r), hcmul(ch, y3, y3r));
          }
        }
        if (PP && r == 1 && wg == 0) bar_arrive(7, 256);
        uint32_t sh[8], uh[7], ur[7];
#pragma unroll
        for (int e = 0; e < 8; e++) {
          sh[e] = pack_h2(s[e].x, s[e].y);
          if ((e & 3) == 3) stsm4(st + (13 + e) * 144, sh[e - 3], sh[e - 2], sh[e - 1], sh[e]);
          if (e < 7) { uh[e] = pack_h2(u[e].x, u[e].y); ur[e] = pack_h2(-u[e].y, u[e].x); }
        }
        const cplx t8 = cmul(s[7], u[7]);
        const uint32_t th = pack_h2(t8.x, t8.y);
        __syncwarp();
        uint32_t af[4][4];
#pragma unroll
        for (int k = 0; k < 4; k++) {
          ldsm4(la + k * 32, af[k]);
          mma_f16(k0, af[k], 0x3c00u, 0x3c00u);
        }
#pragma unroll
        for (int j = 1; j < 6; j++) {
          uint32_t bf[2][4];
          ldsm4(lb + (j - 1) * 8 * 144, bf[0]);
          ldsm4(lb + (j - 1) * 8 * 144 + 64, bf[1]);
          if (j < 5) {
            uint32_t v[8];
#pragma unroll
            for (int n = 0; n < 8; n++) {
              v[n] = j == 1 ? hcmul(sh[n], uh[0], ur[0])
                               : j == 2 ? hcmul(sh[2 * (n & 3) + 1], uh[1 + (n >> 2)], ur[1 + (n >> 2)])
                               : j == 3 ? hcmul(sh[4 * (n & 1) + 3], uh[3 + (n >> 1)], ur[3 + (n >> 1)])
                               : n == 0 ? th : hcmul(th, uh[n ? n - 1 : 0], ur[n ? n - 1 : 0]);
              if ((n & 3) == 3) stsm4(st + (13 + 8 * j + n) * 144, v[n - 3], v[n - 2], v[n - 1], v[n]);
            }
          }
#pragma unroll
          for (int k = 0; k < 2; k++) {
            mma_f16(kacc[j - 1], af[2 * k], bf[k][0], bf[k][1]);
            mma_f16(kacc[j - 1], af[2 * k + 1], bf[k][2], bf[k][3]);
          }
          __syncwarp();
        }
      }
      PROF(18);
      const uint32_t kp = wa + 16;
      stsm4(kp + lane * 16, pack_h2(kacc[0][0], kacc[0][1]), pack_h2(kacc[0][2], kacc[0][3]), pack_h2(kacc[1][0], kacc[1][1]), pack_h2(kacc[1][2], kacc[1][3]));
      asm volatile("stmatrix.sync.aligned.m8n8.x2.trans.shared.b16 [%0], {%1,%2};" ::"r"(kp + 1024 + (lane & 7) * 32 + (lane & 8) * 2),
                   "r"(pack_h2(kacc[4][0], kacc[4][1])), "r"(pack_h2(kacc[4][2], kacc[4][3])) : "memory");
#pragma unroll
      for (int hh = 0; hh < 2; hh++) {
        sts32(kp + 512 + hh * 64 + (32 * (q >> 1) + 2 * g + (q & 1)) * 4, pack_h2(kacc[2][2 * hh], kacc[2][2 * hh + 1]));
        sts32(kp + 768 + hh * 32 + (16 * q + g) * 4, pack_h2(kacc[3][2 * hh], kacc[3][2 * hh + 1]));
      }
      if (lane == 0) sts32(kp - 4, pack_h2(0.f, k0[0]));
      bar_sync(3 + wg, 128);
      PROF(21);
      const int u = tid & 63;
      const uint32_t ks = sb + SM_KG + (warp >> 1) * 16384 + u * 4, tb = sb + SM_PART + (warp >> 1) * 16384;
      uint32_t pv[4], v[4];
#pragma unroll
      for (int j = 0; j < 4; j++) {
        pv[j] = hadd2(lds32(ks + 12 + j * 256), lds32(ks + 8192 + 12 + j * 256));
        v[j] = hadd2(lds32(ks + 16 + j * 256), lds32(ks + 8192 + 16 + j * 256));
      }
#pragma unroll
      for (int j = 0; j < 4; j++)
        sts128(tb + T_TAB + 128 + u * 16 + j * 1024, __byte_perm(v[j], pv[j], 0x7610), __byte_perm(v[j], 0, 0x1010), __byte_perm(v[j], 0, 0x1032), __byte_perm(v[j], 0, 0x3232));
      if (u == 0 || u == 63) sts32(tb + (u ? T_EDGE : T_TAB + 120), u ? v[3] & 0xffff0000u : pv[0] >> 16);
    }
    PROF(2);
    asm volatile("setmaxnreg.inc.sync.aligned.u32 " RC ";");
    const int un = (tid >> 3) * 32 + (tid & 7);
    uint4* xt = S->xt + b * 1024 + un;
    uint4 sv[4], xv[4];
    bar_sync(12 + wg, 256);
    PROF(22);
    {
      const uint32_t tbA = sb + SM_PART + wg * 32768;
      uint32_t q0A[32], q1A[32], q0B[32], q1B[32];
      load_taps<0>(q0A, 0, ad, st0);
      load_taps<0>(q0B, 16384, ad, st0);
      expand_taps(q0A);
      sched_fence();
#pragma unroll
    for (int i = 0; i < 4; i++) { xv[i] = ld_relaxed128(xt + i * 8); sv[i] = ld_relaxed128(S->stats + un + i * 8); }
      sched_fence();
      load_taps<1>(q1A, 0, ad, st0);
      expand_taps(q0B);
      sched_fence();
      load_taps<1>(q1B, 16384, ad, st0);
      expand_taps(q1A);
      expand_taps(q1B);
      sched_fence();
      PROF(23);
      {
#pragma unroll 1
        for (int it = 0; it < kSpin; it++) {
          uint32_t ok = ~0u;
#pragma unroll
          for (int i = 0; i < 4; i++) ok = min(min(ok, xv[i].x), min(sv[i].y, sv[i].w));
          if (ok) break;
#pragma unroll
          for (int i = 0; i < 4; i++) { xv[i] = ld_relaxed128(xt + i * 8); sv[i] = ld_relaxed128(S->stats + un + i * 8); }
        }
        PROF(15);
        uint32_t v[4][4];
#pragma unroll
        for (int i = 0; i < 4; i++) {
          xv[i] = make_uint4(~xv[i].x, xv[i].z, xv[i].y, xv[i].w);
          const float r0 = __uint_as_float(sv[i].y), n0 = __uint_as_float(sv[i].x), r1 = __uint_as_float(sv[i].w), n1 = __uint_as_float(sv[i].z);
          v[0][i] = pack_h2(fmaf(blo(xv[i].x), r0, n0), fmaf(blo(xv[i].y), r1, n1));
          v[1][i] = pack_h2(fmaf(bhi(xv[i].x), r0, n0), fmaf(bhi(xv[i].y), r1, n1));
          v[2][i] = pack_h2(fmaf(blo(xv[i].z), r0, n0), fmaf(blo(xv[i].w), r1, n1));
          v[3][i] = pack_h2(fmaf(bhi(xv[i].z), r0, n0), fmaf(bhi(xv[i].w), r1, n1));
        }
        const uint32_t va = sb + SM_V + ((tid >> 3) & 1) * V_PITCH + (8 + (tid & 7) + 8 * (tid >> 4)) * 16;
#pragma unroll
        for (int c = 0; c < 4; c++) sts128(va + 2 * c * V_PITCH, v[c][0], v[c][1], v[c][2], v[c][3]);
        const uint32_t xa = sb + SM_XS + wg * XS_STEP + (tid & 127) * 16;
#pragma unroll
        for (int c = 0; c < 4; c++) {
          uint32_t u[4];
#pragma unroll
          for (int i = 0; i < 4; i++) u[i] = __byte_perm(c < 2 ? xv[i].x : xv[i].z, c < 2 ? xv[i].y : xv[i].w, (c & 1) ? 0x7632 : 0x5410);
          sts128(xa + c * 2048, u[0], u[1], u[2], u[3]);
        }
        fence_async();
        bar_arrive(10 + wg, 256);
      }
      if (wg) bar_sync(10, 256);
      else bar_sync(3, 128);
      if (lane == 0) mbar_arrive(bars + 8 * (B_V + wg));
      PROFT(3);
      const uint64_t vA = mkdesc(sb + SM_V + 4 * wg * V_PITCH + 128, V_PITCH, 128, 0), vB = vA + 2 * V_PITCH / 16;
      const uint32_t pa = tbA + (2 * w + ((lane >> 3) & 1)) * 1024 + (lane >> 4) * 128 + (lane & 7) * 16;
      uint32_t L[16], M[16], L1[8], M1[8], L2[16], M2[16], eA[8], eB[8];
      wg_fence();
      conv64<true>(L, q0A, vA);
      conv32(L1, q1A, vA);
      wg_commit();
      conv64<true>(M, q0B, vB);
      conv32(M1, q1B, vB);
      wg_commit();
      wg_wait<1>();
#pragma unroll
      for (int i = 0; i < 8; i++) L[8 + i] = hadd2(L[8 + i], L1[i]);
      store_partial(L, pa);
      if (wg == 0) bar_sync(11, 256);
      wg_fence();
      conv64<true>(L2, q1A, vA + 32);
      wg_commit();
      wg_wait<1>();
#pragma unroll
      for (int i = 0; i < 8; i++) M[8 + i] = hadd2(M[8 + i], M1[i]);
      store_partial(M, pa + 16384);
      bar_sync(3 + wg, 128);
      PROF(4);
      finish_h<0, 0, 2>(wg, tid & 127);
      fence_async();
      bar_arrive(8, LATEW ? kThreads : 288);
      sched_fence();
      PROF(24);
      wg_fence();
      conv64<false>(L2, q0A, vA + 64);
      conv64<true>(M2, q1B, vB + 32);
      wg_commit();
      sched_fence();
      edge_load(eA, 0, ad);
      edge_load(eB, 16384, ad);
      bar_sync(12 + wg, 128 + 32 * NWW);
      fence_async();
      wg_fence();
      PROF(26);
      const uint64_t rA = mkdesc(tbA + T_FAR, 1536, 128, 0), wA = mkdesc(tbA + T_TAB, 2048, 128, 0);
      far_mma(L2, eA, vA, wA, rA);
      wg_commit();
      far_mma(M2, eB, vB, wA + 1024, rA + 1024);
      conv64<false>(M2, q0B, vB + 64);
      wg_commit();
      wg_wait<1>();
      bar_sync(3 + wg, 128);
      store_partial(L2, pa + 8192);
      bar_sync(3 + wg, 128);
      finish_h<1, 0, 1>(wg, tid & 127);
      wg_wait<0>();
      bar_sync(3 + wg, 128);
      store_partial(M2, pa + 16384 + 8192);
      bar_sync(3 + wg, 128);
      PROF(25);
      finish_h<1, 1, 2>(wg, tid & 127);
      fence_async();
      bar_arrive(wg ? 9 : 15, 160);
      sched_fence();
    }
    PROFT(5);
    uint32_t X[128];
    RowC c0, c1;
    uint32_t mb0, mb1;
    const uint32_t sta = sb + SM_HST + wg * XS_STEP + (lane >> 4) * 128 + (lane & 7) * 16;
    const int n8 = 2 * w + ((lane >> 3) & 1);
    const uint32_t frag = ((lane >> 4) * 8 + (lane & 7)) * 128 + ((n8 ^ (lane & 7)) * 16);
#pragma unroll 1
    for (int pass = 0; pass < 2; pass++) {
      float acc[64];
      if (pass == 0) {
        const uint32_t xb = bars + 8 * (B_XFULL + 4 * wg), xe = sb + SM_XST + frag + (tj & 1) * 8192, xo = xe ^ 8192;
        uint4* sp = S->st2 + ti * 512 + warp * 8 + g;
        uint4 pa, pb;
        float s0 = 0.f, s1 = 0.f, q0 = 0.f, q1 = 0.f;
        mbar_wait_data(xb, 0);
        PROFT(6);
#pragma unroll
        for (int k = 0; k < 8; k++) ldsm4t(((k & 4) ? xo : xe) + (k & 3) * 2048, X + 4 * k);
#pragma unroll
        for (int st = 0; st < 8; st++) {
          gemm1_stage(acc, X + 16 * st, st, st == 0 PROF_PASS);
          if (st == GA && wg == 1) bar_arrive(1, 256);
          if ((st & 1) == 0 && lane == 0) mbar_arrive(xb + 8 * (B_XFREE - B_XFULL + st / 2) + (X[16 * st + 31] & blockIdx.y));
          if (st < 6) {
            if ((st & 1) == 0) mbar_wait_data(xb + 4 * st + 8, 0);
#pragma unroll
            for (int k = 0; k < 4; k++) ldsm4t(((st & 1) ? xo : xe) + (st / 2 + 1) * 16384 + k * 2048, X + 16 * st + 32 + 4 * k);
          }
          if (STF && st < 2) sched_fence();
          if (st < 2) {
#pragma unroll
            for (int i = 4 * st; i < 4 * st + 4; i++) {
              float lo = blo(X[2 * i]), hi = bhi(X[2 * i]);
              s0 += lo + hi; q0 = fmaf(lo, lo, fmaf(hi, hi, q0));
              lo = blo(X[2 * i + 1]); hi = bhi(X[2 * i + 1]);
              s1 += lo + hi; q1 = fmaf(lo, lo, fmaf(hi, hi, q1));
            }
          }
          if (STF && st == 0) asm volatile("" : "+f"(s0), "+f"(s1), "+f"(q0), "+f"(q1));
          if (st == 1 || st == 2) {
            s0 += __shfl_xor_sync(0xffffffffu, s0, st); s1 += __shfl_xor_sync(0xffffffffu, s1, st);
            q0 += __shfl_xor_sync(0xffffffffu, q0, st); q1 += __shfl_xor_sync(0xffffffffu, q1, st);
          }
          if (st == 2 && q == 0) st_relaxed128(sp + tj * 64, __float_as_uint(s0), __float_as_uint(q0) | 1u, __float_as_uint(s1), __float_as_uint(q1) | 1u);
          if (st == PST) {
            pa = ld_relaxed128(sp + 128 * q);
            pb = ld_relaxed128(sp + 128 * q + 64);
          }
          if (st == 7) mbar_wait_data(bars + 8 * B_CS, 0);
          if (st > 0) {
            wg_wait<1>();
            if (lane == 0) mbar_arrive(bars + 8 * (B_EMPTY1 + st - 1));
          }
        }
        const uint32_t csa = sb + SM_CS + q * 16;
        uint4 cs[8];
        cs[0] = lds128(csa); cs[1] = lds128(csa + 64);
        wg_wait<0>();
        if (lane == 0) mbar_arrive(bars + 8 * (B_EMPTY1 + 7));
        for (int it = 0; (pa.y == 0 || pa.w == 0 || pb.y == 0 || pb.w == 0) && it < kSpin; it++) {
          pa = ld_relaxed128(sp + 128 * q);
          pb = ld_relaxed128(sp + 128 * q + 64);
        }
        s0 = __uint_as_float(pa.x) + __uint_as_float(pb.x), q0 = __uint_as_float(pa.y) + __uint_as_float(pb.y);
        s1 = __uint_as_float(pa.z) + __uint_as_float(pb.z), q1 = __uint_as_float(pa.w) + __uint_as_float(pb.w);
#pragma unroll
        for (int o = 1; o < 4; o <<= 1) {
          s0 += __shfl_xor_sync(0xffffffffu, s0, o); s1 += __shfl_xor_sync(0xffffffffu, s1, o);
          q0 += __shfl_xor_sync(0xffffffffu, q0, o); q1 += __shfl_xor_sync(0xffffffffu, q1, o);
        }
        const float m0 = s0 * (1.f / kD), m1 = s1 * (1.f / kD);
        const float r0 = rsq(fmaxf(q0 * (1.f / kD) - m0 * m0, 0.f) + 1e-5f), r1 = rsq(fmaxf(q1 * (1.f / kD) - m1 * m1, 0.f) + 1e-5f);
        c0 = {0.7978845608028654f * r0, 0.035677408136300125f * r0 * r0 * r0, 0.5f * r0 * r0};
        c1 = {0.7978845608028654f * r1, 0.035677408136300125f * r1 * r1 * r1, 0.5f * r1 * r1};
        mb0 = pack_b2(-m0, -m0);
        mb1 = pack_b2(-m1, -m1);
#pragma unroll
        for (int J = 0; J < 8; J++) {
          if (J < 6) cs[J + 2] = lds128(csa + (J + 2) * 64);
          float* a = acc + 4 * J;
          a[0] = fmaf(-m0, __uint_as_float(cs[J].x), a[0]); a[1] = fmaf(-m0, __uint_as_float(cs[J].y), a[1]);
          a[2] = fmaf(-m1, __uint_as_float(cs[J].x), a[2]); a[3] = fmaf(-m1, __uint_as_float(cs[J].y), a[3]);
          a[32] = fmaf(-m0, __uint_as_float(cs[J].z), a[32]); a[33] = fmaf(-m0, __uint_as_float(cs[J].w), a[33]);
          a[34] = fmaf(-m1, __uint_as_float(cs[J].z), a[34]); a[35] = fmaf(-m1, __uint_as_float(cs[J].w), a[35]);
        }
      } else {
#pragma unroll
        for (int i = 0; i < 16; i++) center(X[i], (i & 1) ? mb1 : mb0);
#pragma unroll
        for (int st = 0; st < 8; st++) {
          if (st == GATE2 && (STRICT || wg == 0)) bar_sync(wg ? 6 : 1, 256);
          gemm1_stage(acc, X + 16 * st, 8 + st, st == 0 PROF_PASS);
          if (st == GA && (STRICT || wg == 1)) bar_arrive(wg ? 14 : 6, 256);
          if (st == 5) mbar_wait_data(bars + 8 * (B_HEMPTY + wg), 0);
          if (st < 7) {
#pragma unroll
            for (int i = 16 * st + 16; i < 16 * st + 32; i++) center(X[i], (i & 1) ? mb1 : mb0);
          }
          if (st > 0) {
            wg_wait<1>();
            if (lane == 0) mbar_arrive(bars + 8 * (B_EMPTY1 + (7 + st) % 12));
          }
        }
        wg_wait<0>();
        if (lane == 0) mbar_arrive(bars + 8 * (B_EMPTY1 + 3));
      }
      PROFV(7 + 2 * pass, 7);
      if (FAST1 && wg > pass) epilogue1<8, 0>(acc, sta + n8 * 1024, c0, c1);
      else epilogue1<8, PACEE>(acc, sta + n8 * 1024, c0, c1);
      fence_async();
      __syncwarp();
      if (lane == 0) mbar_arrive(bars + 8 * (B_HFULL + wg));
      PROFV(8 + 2 * pass, 8);
    }
    {
      float acc[48];
#pragma unroll
      for (int st = 0; st < 8; st++) {
        if (st == GATE3 && (STRICT > 1 || wg == 0)) bar_sync(wg ? 4 : 14, 256);
        mbar_wait_data(bars + 8 * (B_FULL1 + 4 + st), 1);
        PROF2(48 + st);
        const uint64_t db = mkdesc(sb + SM_RING + (8 + st) * 12288, 128, 1024, 0);
        wg_fence();
#pragma unroll
        for (int k = 0; k < 4; k++) {
          const uint32_t* a = X + 16 * st + 4 * k;
          if ((st | k) == 0) g1_n96i(acc, a[0], a[1], a[2], a[3], db);
          else g1_n96(acc, a[0], a[1], a[2], a[3], db + k * 16, 1);
        }
        wg_commit();
        if (st == GA && (STRICT > 1 || wg == 1)) bar_arrive(wg ? 7 : 4, GS && wg ? 288 : 256);
        if (st == GSPOS && tid == 0) asm volatile("red.relaxed.gpu.global.add.u32 [%0], %1;" ::"l"(&S->cnt[(C_G2 + ((b + GOFF) & 127) / GS) * 32]), "r"(128 / GS) : "memory");
        if (st == 5) mbar_wait_data(bars + 8 * (B_HEMPTY + wg), 1);
        if (st > 0) {
          wg_wait<1>();
          if (lane == 0) mbar_arrive(bars + 8 * (B_EMPTY1 + 3 + st));
        }
      }
      wg_wait<0>();
      if (lane == 0) mbar_arrive(bars + 8 * (B_EMPTY1 + 11));
      PROFT(11);
      epilogue1<6, PACE3>(acc, sta + n8 * 768, c0, c1);
      fence_async();
      __syncwarp();
      if (lane == 0) mbar_arrive(bars + 8 * (B_HFULL + wg));
      PROF(12);
    }
    if (wg == 0) {
      uint32_t res[32];
      const uint32_t ra = sb + SM_OST + (8 * n8 + (lane & 7)) * 128 + (((lane >> 4) ^ (lane & 7)) * 16);
      mbar_wait_data(bars + 8 * B_FULL2, 0);
#pragma unroll
      for (int J = 0; J < 16; J += 2) ldsm4((ra ^ ((J & 7) * 16)) + (J >> 3) * 8192, res + 2 * J);
      bar_sync(7, GS ? 288 : 256);
      PROF(27);
      float acc[64];
#pragma unroll 1
      for (int n = 0; n < 16 - RESPOS; n++) gemm2_stage<4>(acc, n, lane PROF_PASS);
      PROF(28);
#pragma unroll 1
      for (int n = 16; n < 23; n++) gemm2_stage<3>(acc, n, lane PROF_PASS);
      gemm2_stage<1>(acc, 23, lane PROF_PASS);
      wg_wait<0>();
      PROF(13);
      if (ONEF) {
        store_out<16>(acc, res, sb + SM_OST + frag);
        bar_arrive(8, 160);
        bar_arrive(9, 160);
      } else
#pragma unroll
      for (int i = 0; i < NQ; i++) {
        store_out<16 / NQ>(acc + i * (64 / NQ), res + i * (32 / NQ), sb + SM_OST + i * (16384 / NQ) + frag);
        bar_arrive(8 + i, 160);
      }
    } else {
      mbar_wait(bars + 8 * (B_HRDY + 1), 0);
#pragma unroll 1
      for (int n = 12 + w; n < 24; n += 4) {
        load_wd(n, ui, uj, &md, &md48, &mr);
        if (n - w == 16) { PROF(27); mbar_wait(bars + 8 * B_WS, 1); PROF(28); }
        load_h(n, S->H + ui * 24576);
        PROF2(64 + n);
      }
      if (w < NQ) {
        if (elect()) asm volatile("prefetch.tensormap [%0];" ::"l"(&mo) : "memory");
        bar_sync(8 + w, 160);
        if (lane == 0) {
          asm volatile("cp.async.bulk.tensor.4d.global.shared::cta.bulk_group [%0, {%2, %3, %4, %5}], [%1];" ::"l"(&mo), "r"(sb + SM_OST + w * (16384 / NQ)), "r"(64 * uj),
                       "r"(0), "r"(ui & 1), "r"(NQ == 2 ? 64 * w + 8 * (ui >> 1) : 64 * (w >> 1) + 4 * (w & 1) + 8 * (ui >> 1)) : "memory");
          asm volatile("cp.async.bulk.commit_group;" ::: "memory");
          asm volatile("cp.async.bulk.wait_group.read 0;" ::: "memory");
        }
      }
    }
    PROFT(14);
  }
}

typedef CUresult (*EncodeFn)(CUtensorMap*, CUtensorMapDataType, cuuint32_t, void*, const cuuint64_t*, const cuuint64_t*, const cuuint32_t*,
                             const cuuint32_t*, CUtensorMapInterleave, CUtensorMapSwizzle, CUtensorMapL2promotion, CUtensorMapFloatOOBfill);

void make_map(EncodeFn fn, CUtensorMap* m, void* p, int rows, int cols, int box_rows) {
  cuuint64_t dims[2] = {(cuuint64_t)cols, (cuuint64_t)rows};
  cuuint64_t strides[1] = {(cuuint64_t)cols * 2};
  cuuint32_t box[2] = {64, (cuuint32_t)box_rows};
  cuuint32_t es[2] = {1, 1};
  fn(m, CU_TENSOR_MAP_DATA_TYPE_BFLOAT16, 2, p, dims, strides, box, es, CU_TENSOR_MAP_INTERLEAVE_NONE, CU_TENSOR_MAP_SWIZZLE_128B,
     CU_TENSOR_MAP_L2_PROMOTION_L2_128B, CU_TENSOR_MAP_FLOAT_OOB_FILL_NONE);
}

}

extern "C" void kernel_launch(void* const* d_in, const int* in_sizes, int n_in, void* d_out, int out_size) {
  static EncodeFn fn = nullptr;
  static Scratch* scratch = nullptr;
  static void* taps = nullptr;
  if (!fn) {
    cudaGetSymbolAddress((void**)&scratch, g_scratch);
    cudaGetSymbolAddress(&taps, g_taps);
    cudaDriverEntryPointQueryResult st;
    cudaGetDriverEntryPoint("cuTensorMapEncodeTiled", (void**)&fn, cudaEnableDefault, &st);
    cudaFuncSetAttribute(fused_kernel, cudaFuncAttributeMaxDynamicSharedMemorySize, SM_TOTAL);
  }
  CUtensorMap mg, mu, md, md48, mx, mh, mr, mo;
  CUtensorMap m8[2];
  for (int i = 0; i < 2; i++) {
    cuuint64_t dims[3] = {8, 512, 172}, strides[2] = {2752, 16};
    cuuint32_t box[3] = {8, 64, 6}, es[3] = {1, 1, 1};
    fn(&m8[i], CU_TENSOR_MAP_DATA_TYPE_BFLOAT16, 3, d_in[8 + i], dims, strides, box, es, CU_TENSOR_MAP_INTERLEAVE_NONE, CU_TENSOR_MAP_SWIZZLE_NONE,
       CU_TENSOR_MAP_L2_PROMOTION_L2_128B, CU_TENSOR_MAP_FLOAT_OOB_FILL_NONE);
  }
  make_map(fn, &mh, scratch->h, 1024, 1024, 128);
  make_map(fn, &mr, scratch->h, 1024, 1024, 64);
  {
    cuuint64_t dims[4] = {512, 8, 2, 128}, strides[3] = {1024, 8192, 16384};
    cuuint32_t box[4] = {64, 8, 1, 16 / NQ}, es[4] = {1, 1, 1, 1};
    fn(&mo, CU_TENSOR_MAP_DATA_TYPE_BFLOAT16, 4, d_out, dims, strides, box, es, CU_TENSOR_MAP_INTERLEAVE_NONE, CU_TENSOR_MAP_SWIZZLE_128B,
       CU_TENSOR_MAP_L2_PROMOTION_NONE, CU_TENSOR_MAP_FLOAT_OOB_FILL_NONE);
  }
  make_map(fn, &mx, scratch->xt, 128, 8192, 128);
  make_map(fn, &mg, d_in[8], kD, kF, 64);
  make_map(fn, &mu, d_in[9], kD, kF, 64);
  make_map(fn, &md, d_in[10], kF, kD, 64);
  make_map(fn, &md48, d_in[10], kF, kD, 48);
  Params P;
  P.x = (const uint32_t*)d_in[0];
  P.lar = (const uint32_t*)d_in[1];
  P.aim = (const uint32_t*)d_in[2];
  P.cre = (const uint32_t*)d_in[3];
  P.cim = (const uint32_t*)d_in[4];
  P.ldt = (const uint32_t*)d_in[5];
  P.dsk = (const uint32_t*)d_in[6];
  P.scratch = scratch;
  P.taps = taps;
  P.wg = (const uint4*)d_in[8];
  P.wu = (const uint4*)d_in[9];
  P.wd = (const uint4*)d_in[10];
  fused_kernel<<<kCtas + 4, kThreads, SM_TOTAL, cudaStreamPerThread>>>(P, mg, mu, md, md48, mx, mh, mr, mo, m8[0], m8[1]);
}
```
